```python
import torch

def _softmax(x, axis=-1):
    return torch.softmax(x, dim=axis)
def _gelu(x):
    return torch.nn.functional.gelu(x, approximate="tanh")
def _silu(x):
    return torch.nn.functional.silu(x)
def _sigmoid(x):
    return torch.sigmoid(x)
def _layernorm(x, axis=-1, eps=1e-5):
    m = x.mean(dim=axis, keepdim=True)
    v = x.var(dim=axis, keepdim=True, unbiased=False)
    return (x - m) / torch.sqrt(v + eps)
def _scatter_add(tgt, idx, src, axis=0):
    return tgt.clone().index_add_(axis, idx, src)
def _segment_sum(src, seg, n):
    out = torch.zeros((n,) + src.shape[1:], dtype=src.dtype)
    return out.index_add_(0, seg, src)
def _pad(x, pw):
    flat = tuple(v for pair in reversed(pw) for v in pair)
    return torch.nn.functional.pad(x, flat)

kernel_name = 'parallel_sum__compressed_kv_cla__moe_arch_mod__prompt'

def setup_inputs():

    _w = (lambda a: (lambda t: t.to(torch.bfloat16) if t.is_floating_point() else t)(torch.as_tensor(a)))
    def _A_setup():
        B, H, Sq, Sk, D, M = 1, 32, 2048, 2048, 128, 512
        Dc = 4 * D
        return {
            "x": _w((lambda *s: torch.randn(*s, dtype=torch.bfloat16) * 0.05)(B, Sq, M)),
            "c_kv": _w((lambda *s: torch.randn(*s, dtype=torch.bfloat16) * 1.6)(B, Sk, Dc)),
            "w_q": _w((lambda *s: torch.randn(*s, dtype=torch.bfloat16) * 1.6)(M, H, D) * (M ** -0.5)),
            "w_uk": _w((lambda *s: torch.randn(*s, dtype=torch.bfloat16) * 1.6)(Dc, H, D) * (Dc ** -0.5)),
            "w_uv": _w((lambda *s: torch.randn(*s, dtype=torch.bfloat16) * 1.6)(Dc, H, D) * (Dc ** -0.5)),
            "w_o": _w((lambda *s: torch.randn(*s, dtype=torch.bfloat16) * 1.6)(H, D, M) * ((H * D) ** -0.5)),
        }
    _A_in = _A_setup()

    def _B_setup():
        B, S, D, F, C = 1, 2048, 512, 1376, 1
        return {
            "x": _w((lambda *s: torch.randn(*s, dtype=torch.bfloat16) * 0.05)(B, S, D)),
            "w_r": _w((lambda *s: torch.randn(*s, dtype=torch.bfloat16) * 1.6)(D)),
            "w_gate": _w((lambda *s: torch.randn(*s, dtype=torch.bfloat16) * 0.1)(D, F)),
            "w_up": _w((lambda *s: torch.randn(*s, dtype=torch.bfloat16) * 0.1)(D, F)),
            "w_down": _w((lambda *s: torch.randn(*s, dtype=torch.bfloat16) * 0.1)(F, D)),
        }
    _B_in = _B_setup()

    return {
        "A_x": _A_in["x"],
        "A_c_kv": _A_in["c_kv"],
        "A_w_q": _A_in["w_q"],
        "A_w_uk": _A_in["w_uk"],
        "A_w_uv": _A_in["w_uv"],
        "A_w_o": _A_in["w_o"],
        "B_x": _B_in["x"],
        "B_w_r": _B_in["w_r"],
        "B_w_gate": _B_in["w_gate"],
        "B_w_up": _B_in["w_up"],
        "B_w_down": _B_in["w_down"],
    }

def reference(A_x, A_c_kv, A_w_q, A_w_uk, A_w_uv, A_w_o, B_x, B_w_r, B_w_gate, B_w_up, B_w_down):
    def _A_ref(x, c_kv, w_q, w_uk, w_uv, w_o):
        B, Sq, M = x.shape[0], x.shape[1], x.shape[2]
        Sk = c_kv.shape[1]
        H, D = w_q.shape[1], w_q.shape[2]
        q = torch.einsum("bqm,mhd->bhqd", x, w_q)
        k = torch.einsum("bkc,chd->bhkd", c_kv, w_uk)
        v = torch.einsum("bkc,chd->bhkd", c_kv, w_uv)
        scores = torch.einsum("bhqd,bhkd->bhqk", q, k) * (D ** -0.5)
        off = Sk - Sq
        qi = torch.arange(Sq)[:, None]
        kj = torch.arange(Sk)[None, :]
        cmask = kj <= (qi + off)
        scores = torch.where(cmask[None, None], scores, -1e9)
        p = _softmax(scores, axis=-1)
        ctx = torch.einsum("bhqk,bhkd->bhqd", p, v)
        return torch.einsum("bhqd,hdm->bqm", ctx, w_o)

    def _B_ref(x, w_r, w_gate, w_up, w_down):
        B, S, D = x.shape
        C = 1
        r = x @ w_r
        idx = torch.argsort(-r, axis=-1)[:, :C]
        idx_e = (lambda x, n, axis: torch.repeat_interleave(x, n, dim=axis))(idx.reshape(B, C, 1), D, axis=2)
        x_sel = (lambda x, i, axis: torch.take_along_dim(x, i, dim=axis))(x, idx_e, axis=1)
        g = _silu(x_sel @ w_gate)
        u = x_sel @ w_up
        y = (g * u) @ w_down
        r_sel = _sigmoid((lambda x, i, axis: torch.take_along_dim(x, i, dim=axis))(r, idx, axis=1))
        y = y * r_sel.reshape(B, C, 1)
        b_off = (torch.arange(B) * S).reshape(B, 1)
        flat_idx = (idx + b_off).reshape(B * C)
        zero = (x * 0.0).reshape(B * S, D)
        upd = _scatter_add(zero, flat_idx, y.reshape(B * C, D), axis=0)
        return x + upd.reshape(B, S, D)

    x = A_x
    xn = _layernorm(x, axis=-1)
    return x + _A_ref(xn, A_c_kv, A_w_q, A_w_uk, A_w_uv, A_w_o) + _B_ref(xn, B_w_r, B_w_gate, B_w_up, B_w_down)
```

```cpp
#include <cuda_runtime.h>
#include <cuda_bf16.h>
#include <cuda.h>
#include <stdint.h>

namespace {

constexpr int SEQ = 2048, DM = 512, NH = 32, FF = 1376;
constexpr int NSLOT = 6;
constexpr int TILE = 32768;
constexpr int HALF = 16384;
constexpr int SMEM_STG = NSLOT * TILE;
constexpr int SMEM_BAR = SMEM_STG + 32768;
constexpr int SMEM_TOTAL = SMEM_BAR + 256 + 1024;
constexpr int NCTA = 132;
constexpr int SPIN_LIMIT = 1 << 22;

constexpr int F_LN = 0;
constexpr int F_HEAD = 16;
constexpr int F_CTX = 48;
constexpr int F_PART = 112;
constexpr int F_MOE = 368;
constexpr int F_COUNT = 369;

__device__ __align__(1024) __nv_bfloat16 g_xn[SEQ * DM];
__device__ float g_r[SEQ];
__device__ __align__(1024) uint8_t g_qkv[3ull * NH * 16 * TILE];
__device__ __align__(1024) uint8_t g_ctx[1ull * NH * 16 * TILE];
__device__ __align__(1024) float4 g_part[128 * 256 * 8];
__device__ float g_ypart[4 * DM];
__device__ int g_sel;
__device__ float g_gate;
__device__ unsigned g_flags[F_COUNT * 32];
__device__ unsigned g_epoch[NCTA];
#define TL(i)

__device__ __forceinline__ uint32_t smem_u32(const void* p) { return (uint32_t)__cvta_generic_to_shared(p); }
__device__ __forceinline__ void mbar_init(uint32_t bar, int cnt) { asm volatile("mbarrier.init.shared::cta.b64 [%0], %1;" :: "r"(bar), "r"(cnt)); }
__device__ __forceinline__ void mbar_arrive(uint32_t bar) { asm volatile("mbarrier.arrive.shared::cta.b64 _, [%0];" :: "r"(bar) : "memory"); }
__device__ __forceinline__ void mbar_arrive_cluster_if(uint32_t bar, bool pred) {
  asm volatile("{\n.reg .pred p;\nsetp.ne.b32 p, %1, 0;\n@p mbarrier.arrive.shared::cluster.b64 _, [%0];\n}" :: "r"(bar), "r"((int)pred) : "memory");
}
__device__ __forceinline__ void mbar_expect(uint32_t bar, int bytes) { asm volatile("mbarrier.arrive.expect_tx.shared::cta.b64 _, [%0], %1;" :: "r"(bar), "r"(bytes) : "memory"); }
__device__ __forceinline__ void mbar_wait(uint32_t bar, uint32_t parity) {
  asm volatile("{\n.reg .pred p, q;\n.reg .b32 n;\n"
               "mbarrier.try_wait.parity.shared::cta.b64 p, [%0], %1;\n@p bra DONE;\nmov.b32 n, 0;\n"
               "LOOP:\nmbarrier.try_wait.parity.shared::cta.b64 p, [%0], %1;\nadd.s32 n, n, 1;\nsetp.lt.s32 q, n, %2;\n@p bra DONE;\n@q bra LOOP;\n"
               "DONE:\n}" :: "r"(bar), "r"(parity), "n"(SPIN_LIMIT) : "memory");
}
__device__ __forceinline__ void bulk_load(uint32_t dst, const void* src, int bytes, uint32_t bar) {
  asm volatile("cp.async.bulk.shared::cluster.global.mbarrier::complete_tx::bytes [%0], [%1], %2, [%3];" :: "r"(dst), "l"(src), "r"(bytes), "r"(bar) : "memory");
}
__device__ __forceinline__ void bulk_load_mc(uint32_t dst, const void* src, int bytes, uint32_t bar) {
  asm volatile("cp.async.bulk.shared::cluster.global.mbarrier::complete_tx::bytes.multicast::cluster [%0], [%1], %2, [%3], %4;" :: "r"(dst), "l"(src), "r"(bytes), "r"(bar), "h"((uint16_t)3) : "memory");
}
__device__ __forceinline__ void tma_load(uint32_t dst, const CUtensorMap* map, int c0, int c1, uint32_t bar) {
  asm volatile("cp.async.bulk.tensor.2d.shared::cluster.global.mbarrier::complete_tx::bytes [%0], [%1, {%3, %4}], [%2];" :: "r"(dst), "l"(map), "r"(bar), "r"(c0), "r"(c1) : "memory");
}
__device__ __forceinline__ void tma_load_mc(uint32_t dst, const CUtensorMap* map, int c0, int c1, uint32_t bar) {
  asm volatile("cp.async.bulk.tensor.2d.shared::cluster.global.mbarrier::complete_tx::bytes.multicast::cluster [%0], [%1, {%3, %4}], [%2], %5;" :: "r"(dst), "l"(map), "r"(bar), "r"(c0), "r"(c1), "h"((uint16_t)3) : "memory");
}
__device__ __forceinline__ void bulk_store(void* dst, uint32_t src, int bytes) {
  asm volatile("cp.async.bulk.global.shared::cta.bulk_group [%0], [%1], %2;" :: "l"(dst), "r"(src), "r"(bytes) : "memory");
}
__device__ __forceinline__ void tma_store(const CUtensorMap* map, int c0, int c1, uint32_t src) {
  asm volatile("cp.async.bulk.tensor.2d.global.shared::cta.bulk_group [%0, {%2, %3}], [%1];" :: "l"(map), "r"(src), "r"(c0), "r"(c1) : "memory");
}
__device__ __forceinline__ void fence_async_smem() { asm volatile("fence.proxy.async.shared::cta;" ::: "memory"); }
__device__ __forceinline__ void fence_async_all() { asm volatile("fence.proxy.async;" ::: "memory"); }
__device__ __forceinline__ void flag_add(int f) { asm volatile("red.release.gpu.global.add.u32 [%0], 1;" :: "l"(&g_flags[f * 32]) : "memory"); }
__device__ __forceinline__ void flag_wait(int f, unsigned target) {
  const unsigned* p = &g_flags[f * 32];
  for (int n = 0; n < SPIN_LIMIT; ++n) {
    unsigned v;
    asm volatile("ld.acquire.gpu.global.u32 %0, [%1];" : "=r"(v) : "l"(p) : "memory");
    if ((int)(v - target) >= 0) break;
  }
}
__device__ __forceinline__ void bar_sync(int id, int n) { asm volatile("bar.sync %0, %1;" :: "r"(id), "r"(n) : "memory"); }
__device__ __forceinline__ void bar_arrive(int id, int n) { asm volatile("bar.arrive %0, %1;" :: "r"(id), "r"(n) : "memory"); }
__device__ __forceinline__ void wg_fence() { asm volatile("wgmma.fence.sync.aligned;" ::: "memory"); }
__device__ __forceinline__ void wg_commit() { asm volatile("wgmma.commit_group.sync.aligned;" ::: "memory"); }
template <int N> __device__ __forceinline__ void wg_wait() { asm volatile("wgmma.wait_group.sync.aligned %0;" :: "n"(N) : "memory"); }
template <int N> __device__ __forceinline__ void reg_fence(float (&d)[N]) {
#pragma unroll
  for (int i = 0; i < N; i++) asm volatile("" : "+f"(d[i]) :: "memory");
}
__device__ __forceinline__ void ldsm4(uint32_t addr, uint32_t& r0, uint32_t& r1, uint32_t& r2, uint32_t& r3) {
  asm volatile("ldmatrix.sync.aligned.m8n8.x4.shared.b16 {%0, %1, %2, %3}, [%4];" : "=r"(r0), "=r"(r1), "=r"(r2), "=r"(r3) : "r"(addr) : "memory");
}
__device__ __forceinline__ void stsm4(uint32_t addr, uint32_t r0, uint32_t r1, uint32_t r2, uint32_t r3) {
  asm volatile("stmatrix.sync.aligned.m8n8.x4.shared.b16 [%0], {%1, %2, %3, %4};" :: "r"(addr), "r"(r0), "r"(r1), "r"(r2), "r"(r3) : "memory");
}
__device__ __forceinline__ uint32_t pack_bf16(float lo, float hi) {
  uint32_t r; asm("cvt.rn.bf16x2.f32 %0, %1, %2;" : "=r"(r) : "f"(hi), "f"(lo)); return r;
}
__device__ __forceinline__ float ex2(float x) { float y; asm("ex2.approx.ftz.f32 %0, %1;" : "=f"(y) : "f"(x)); return y; }
__device__ __forceinline__ float bf_lo(uint32_t v) { return __uint_as_float(v << 16); }
__device__ __forceinline__ float bf_hi(uint32_t v) { return __uint_as_float(v & 0xffff0000u); }
__device__ __forceinline__ float rbf(float x) { return __bfloat162float(__float2bfloat16_rn(x)); }

__device__ __forceinline__ uint64_t desc_k(uint32_t addr) { return (uint64_t)(((addr & 0x3FFFF) >> 4) | (1u << 16)) | ((uint64_t)(64u | (1u << 30)) << 32); }
__device__ __forceinline__ uint64_t desc_mn(uint32_t addr) { return (uint64_t)(((addr & 0x3FFFF) >> 4) | ((uint32_t)(HALF >> 4) << 16)) | ((uint64_t)(64u | (1u << 30)) << 32); }

template<int TB> __device__ __forceinline__ void wgmma_ss_n128(float (&d)[64], uint64_t descA, uint64_t descB, int scaleD) {
  asm volatile("{\n.reg .pred p;\nsetp.ne.b32 p, %66, 0;\n"
    "wgmma.mma_async.sync.aligned.m64n128k16.f32.bf16.bf16 "
    "{%0, %1, %2, %3, %4, %5, %6, %7, %8, %9, %10, %11, %12, %13, %14, %15, "
    "%16, %17, %18, %19, %20, %21, %22, %23, %24, %25, %26, %27, %28, %29, %30, %31, "
    "%32, %33, %34, %35, %36, %37, %38, %39, %40, %41, %42, %43, %44, %45, %46, %47, "
    "%48, %49, %50, %51, %52, %53, %54, %55, %56, %57, %58, %59, %60, %61, %62, %63}, "
    "%64, %65, p, 1, 1, 0, %67;\n}\n"
    : "+f"(d[0]), "+f"(d[1]), "+f"(d[2]), "+f"(d[3]), "+f"(d[4]), "+f"(d[5]), "+f"(d[6]), "+f"(d[7]),
      "+f"(d[8]), "+f"(d[9]), "+f"(d[10]), "+f"(d[11]), "+f"(d[12]), "+f"(d[13]), "+f"(d[14]), "+f"(d[15]),
      "+f"(d[16]), "+f"(d[17]), "+f"(d[18]), "+f"(d[19]), "+f"(d[20]), "+f"(d[21]), "+f"(d[22]), "+f"(d[23]),
      "+f"(d[24]), "+f"(d[25]), "+f"(d[26]), "+f"(d[27]), "+f"(d[28]), "+f"(d[29]), "+f"(d[30]), "+f"(d[31]),
      "+f"(d[32]), "+f"(d[33]), "+f"(d[34]), "+f"(d[35]), "+f"(d[36]), "+f"(d[37]), "+f"(d[38]), "+f"(d[39]),
      "+f"(d[40]), "+f"(d[41]), "+f"(d[42]), "+f"(d[43]), "+f"(d[44]), "+f"(d[45]), "+f"(d[46]), "+f"(d[47]),
      "+f"(d[48]), "+f"(d[49]), "+f"(d[50]), "+f"(d[51]), "+f"(d[52]), "+f"(d[53]), "+f"(d[54]), "+f"(d[55]),
      "+f"(d[56]), "+f"(d[57]), "+f"(d[58]), "+f"(d[59]), "+f"(d[60]), "+f"(d[61]), "+f"(d[62]), "+f"(d[63])
    : "l"(descA), "l"(descB), "r"(scaleD), "n"(TB));
}

template<int TB> __device__ __forceinline__ void wgmma_rs_n128(float (&d)[64], uint32_t a0, uint32_t a1, uint32_t a2, uint32_t a3, uint64_t descB, int scaleD) {
  asm volatile("{\n.reg .pred p;\nsetp.ne.b32 p, %69, 0;\n"
    "wgmma.mma_async.sync.aligned.m64n128k16.f32.bf16.bf16 "
    "{%0, %1, %2, %3, %4, %5, %6, %7, %8, %9, %10, %11, %12, %13, %14, %15, "
    "%16, %17, %18, %19, %20, %21, %22, %23, %24, %25, %26, %27, %28, %29, %30, %31, "
    "%32, %33, %34, %35, %36, %37, %38, %39, %40, %41, %42, %43, %44, %45, %46, %47, "
    "%48, %49, %50, %51, %52, %53, %54, %55, %56, %57, %58, %59, %60, %61, %62, %63}, "
    "{%64, %65, %66, %67}, %68, p, 1, 1, %70;\n}\n"
    : "+f"(d[0]), "+f"(d[1]), "+f"(d[2]), "+f"(d[3]), "+f"(d[4]), "+f"(d[5]), "+f"(d[6]), "+f"(d[7]),
      "+f"(d[8]), "+f"(d[9]), "+f"(d[10]), "+f"(d[11]), "+f"(d[12]), "+f"(d[13]), "+f"(d[14]), "+f"(d[15]),
      "+f"(d[16]), "+f"(d[17]), "+f"(d[18]), "+f"(d[19]), "+f"(d[20]), "+f"(d[21]), "+f"(d[22]), "+f"(d[23]),
      "+f"(d[24]), "+f"(d[25]), "+f"(d[26]), "+f"(d[27]), "+f"(d[28]), "+f"(d[29]), "+f"(d[30]), "+f"(d[31]),
      "+f"(d[32]), "+f"(d[33]), "+f"(d[34]), "+f"(d[35]), "+f"(d[36]), "+f"(d[37]), "+f"(d[38]), "+f"(d[39]),
      "+f"(d[40]), "+f"(d[41]), "+f"(d[42]), "+f"(d[43]), "+f"(d[44]), "+f"(d[45]), "+f"(d[46]), "+f"(d[47]),
      "+f"(d[48]), "+f"(d[49]), "+f"(d[50]), "+f"(d[51]), "+f"(d[52]), "+f"(d[53]), "+f"(d[54]), "+f"(d[55]),
      "+f"(d[56]), "+f"(d[57]), "+f"(d[58]), "+f"(d[59]), "+f"(d[60]), "+f"(d[61]), "+f"(d[62]), "+f"(d[63])
    : "r"(a0), "r"(a1), "r"(a2), "r"(a3), "l"(descB), "r"(scaleD), "n"(TB));
}

template<int TB> __device__ __forceinline__ void wgmma_rs_n64(float (&d)[64], uint32_t a0, uint32_t a1, uint32_t a2, uint32_t a3, uint64_t descB, int scaleD) {
  asm volatile("{\n.reg .pred p;\nsetp.ne.b32 p, %37, 0;\n"
    "wgmma.mma_async.sync.aligned.m64n64k16.f32.bf16.bf16 "
    "{%0, %1, %2, %3, %4, %5, %6, %7, %8, %9, %10, %11, %12, %13, %14, %15, "
    "%16, %17, %18, %19, %20, %21, %22, %23, %24, %25, %26, %27, %28, %29, %30, %31}, "
    "{%32, %33, %34, %35}, %36, p, 1, 1, %38;\n}\n"
    : "+f"(d[0]), "+f"(d[1]), "+f"(d[2]), "+f"(d[3]), "+f"(d[4]), "+f"(d[5]), "+f"(d[6]), "+f"(d[7]),
      "+f"(d[8]), "+f"(d[9]), "+f"(d[10]), "+f"(d[11]), "+f"(d[12]), "+f"(d[13]), "+f"(d[14]), "+f"(d[15]),
      "+f"(d[16]), "+f"(d[17]), "+f"(d[18]), "+f"(d[19]), "+f"(d[20]), "+f"(d[21]), "+f"(d[22]), "+f"(d[23]),
      "+f"(d[24]), "+f"(d[25]), "+f"(d[26]), "+f"(d[27]), "+f"(d[28]), "+f"(d[29]), "+f"(d[30]), "+f"(d[31])
    : "r"(a0), "r"(a1), "r"(a2), "r"(a3), "l"(descB), "r"(scaleD), "n"(TB));
}

struct Cur {
  int slot; uint32_t phase;
  __device__ __forceinline__ void adv() { if (++slot == NSLOT) { slot = 0; phase ^= 1; } }
};

struct Params {
  CUtensorMap ckv, xn, x, wq, wuk, wuv, wo, out;
  const __nv_bfloat16 *px, *w_r, *w_gate, *w_up, *w_down;
};

__device__ __forceinline__ void moe_cta(const Params& P, int q, unsigned ep, uint8_t* smem) {
  float* xs = (float*)smem;
  float* red = xs + DM;
  float* hs = red + 2 * 8 * 344;
  float* sv = hs + 344; int* si = (int*)(sv + 16);
  const int tid = threadIdx.x, lane = tid & 31, warp = tid >> 5;
  if (tid < 16) flag_wait(F_LN + tid, ep * 8);
  __syncthreads();
  float bv = -INFINITY; int bi = 0x7fffffff;
  for (int i = tid; i < SEQ; i += 384) { float v = __ldcg(&g_r[i]); if (v > bv || bi == 0x7fffffff) { bv = v; bi = i; } }
#pragma unroll
  for (int o = 16; o; o >>= 1) {
    float ov = __shfl_xor_sync(~0u, bv, o); int oi = __shfl_xor_sync(~0u, bi, o);
    if (ov > bv || (ov == bv && oi < bi)) { bv = ov; bi = oi; }
  }
  if (lane == 0) { sv[warp] = bv; si[warp] = bi; }
  __syncthreads();
  bv = sv[0]; bi = si[0];
  for (int w = 1; w < 12; w++) { float ov = sv[w]; int oi = si[w]; if (ov > bv || (ov == bv && oi < bi)) { bv = ov; bi = oi; } }
  for (int i = tid; i < DM; i += 384) xs[i] = __bfloat162float(__ldcg(&g_xn[bi * DM + i]));
  __syncthreads();
  const int f0 = q * 344;
  if (tid < 344) {
    const int cg = tid % 43, ksl = tid / 43;
    float ag[8], au[8];
#pragma unroll
    for (int i = 0; i < 8; i++) ag[i] = au[i] = 0.f;
    const __nv_bfloat16* pg = P.w_gate + (size_t)(ksl * 64) * FF + f0 + cg * 8;
    const __nv_bfloat16* pu = P.w_up + (size_t)(ksl * 64) * FF + f0 + cg * 8;
#pragma unroll 8
    for (int k = 0; k < 64; k++) {
      uint4 a = __ldg((const uint4*)(pg + (size_t)k * FF)), b = __ldg((const uint4*)(pu + (size_t)k * FF));
      float xv = xs[ksl * 64 + k];
      ag[0] += xv * bf_lo(a.x); ag[1] += xv * bf_hi(a.x); ag[2] += xv * bf_lo(a.y); ag[3] += xv * bf_hi(a.y);
      ag[4] += xv * bf_lo(a.z); ag[5] += xv * bf_hi(a.z); ag[6] += xv * bf_lo(a.w); ag[7] += xv * bf_hi(a.w);
      au[0] += xv * bf_lo(b.x); au[1] += xv * bf_hi(b.x); au[2] += xv * bf_lo(b.y); au[3] += xv * bf_hi(b.y);
      au[4] += xv * bf_lo(b.z); au[5] += xv * bf_hi(b.z); au[6] += xv * bf_lo(b.w); au[7] += xv * bf_hi(b.w);
    }
#pragma unroll
    for (int i = 0; i < 8; i++) { red[ksl * 344 + cg * 8 + i] = ag[i]; red[(8 + ksl) * 344 + cg * 8 + i] = au[i]; }
  }
  __syncthreads();
  if (tid < 344) {
    float g = 0.f, u = 0.f;
#pragma unroll
    for (int i = 0; i < 8; i++) { g += red[i * 344 + tid]; u += red[(8 + i) * 344 + tid]; }
    g = rbf(g); u = rbf(u);
    g = rbf(g / (1.f + expf(-g)));
    hs[tid] = rbf(g * u);
  }
  __syncthreads();
  {
    const int cg = tid & 63, fs = tid >> 6;
    float ay[8];
#pragma unroll
    for (int i = 0; i < 8; i++) ay[i] = 0.f;
    const __nv_bfloat16* pd = P.w_down + (size_t)f0 * DM + cg * 8;
#pragma unroll 8
    for (int f = fs; f < 344; f += 6) {
      uint4 a = __ldg((const uint4*)(pd + (size_t)f * DM));
      float hv = hs[f];
      ay[0] += hv * bf_lo(a.x); ay[1] += hv * bf_hi(a.x); ay[2] += hv * bf_lo(a.y); ay[3] += hv * bf_hi(a.y);
      ay[4] += hv * bf_lo(a.z); ay[5] += hv * bf_hi(a.z); ay[6] += hv * bf_lo(a.w); ay[7] += hv * bf_hi(a.w);
    }
#pragma unroll
    for (int i = 0; i < 8; i++) red[fs * DM + cg * 8 + i] = ay[i];
  }
  __syncthreads();
  for (int i = tid; i < DM; i += 384) {
    float y = 0.f;
#pragma unroll
    for (int s = 0; s < 6; s++) y += red[s * DM + i];
    g_ypart[q * DM + i] = y;
  }
  if (q == 0 && tid == 0) { g_sel = bi; g_gate = rbf(1.f / (1.f + expf(-bv))); }
  __syncthreads();
  if (tid == 0) { __threadfence(); flag_add(F_MOE); }
}

__device__ __forceinline__ void ln_row(const uint4& a, const uint4& b, const uint4& wa, const uint4& wb, int row, int lane) {
  float v[16] = {bf_lo(a.x), bf_hi(a.x), bf_lo(a.y), bf_hi(a.y), bf_lo(a.z), bf_hi(a.z), bf_lo(a.w), bf_hi(a.w),
                 bf_lo(b.x), bf_hi(b.x), bf_lo(b.y), bf_hi(b.y), bf_lo(b.z), bf_hi(b.z), bf_lo(b.w), bf_hi(b.w)};
  float w[16] = {bf_lo(wa.x), bf_hi(wa.x), bf_lo(wa.y), bf_hi(wa.y), bf_lo(wa.z), bf_hi(wa.z), bf_lo(wa.w), bf_hi(wa.w),
                 bf_lo(wb.x), bf_hi(wb.x), bf_lo(wb.y), bf_hi(wb.y), bf_lo(wb.z), bf_hi(wb.z), bf_lo(wb.w), bf_hi(wb.w)};
  float s = 0.f;
#pragma unroll
  for (int i = 0; i < 16; i++) s += v[i];
#pragma unroll
  for (int o = 16; o; o >>= 1) s += __shfl_xor_sync(~0u, s, o);
  const float mean = s * (1.f / DM);
  float ss = 0.f;
#pragma unroll
  for (int i = 0; i < 16; i++) { float d = v[i] - mean; ss += d * d; }
#pragma unroll
  for (int o = 16; o; o >>= 1) ss += __shfl_xor_sync(~0u, ss, o);
  const float mb = rbf(mean);
  const float sd = rbf(sqrtf(rbf(rbf(ss * (1.f / DM)) + 1e-5f)));
  float r = 0.f;
#pragma unroll
  for (int i = 0; i < 16; i++) { v[i] = rbf(__fdiv_rn(rbf(v[i] - mb), sd)); r += v[i] * w[i]; }
#pragma unroll
  for (int o = 16; o; o >>= 1) r += __shfl_xor_sync(~0u, r, o);
  uint4* dst = (uint4*)(g_xn + (size_t)row * DM);
  dst[lane] = make_uint4(pack_bf16(v[0], v[1]), pack_bf16(v[2], v[3]), pack_bf16(v[4], v[5]), pack_bf16(v[6], v[7]));
  dst[32 + lane] = make_uint4(pack_bf16(v[8], v[9]), pack_bf16(v[10], v[11]), pack_bf16(v[12], v[13]), pack_bf16(v[14], v[15]));
  if (lane == 0) g_r[row] = rbf(r);
}

struct Ctx {
  uint32_t sb;
  uint32_t full0;
  uint32_t rel;
  bool rel_pred;
  uint32_t stg;
  uint32_t stg_full, stg_empty;
  uint32_t stg_phase;
  uint32_t frag_off;
  uint32_t frag_x;
  int w;
  __device__ __forceinline__ void wait(const Cur& c) const { mbar_wait(full0 + 8 * c.slot, c.phase); }
  __device__ __forceinline__ void release(const Cur& c) const { mbar_arrive_cluster_if(rel + 8 * c.slot, rel_pred); }
  __device__ __forceinline__ uint32_t addr(const Cur& c) const { return sb + c.slot * TILE; }
  __device__ __forceinline__ void turn_begin() const { bar_sync(1 + w, 256); }
  __device__ __forceinline__ void turn_end() const { bar_arrive(2 - w, 256); }
  __device__ __forceinline__ uint32_t frag(int jj, int hstride) const { return (jj >> 2) * hstride + frag_off + (((jj & 3) * 32) ^ frag_x); }
  __device__ __forceinline__ void stage_out(const float (&d)[64], float s0, float s1) {
    mbar_wait(stg_empty, stg_phase ^ 1);
#pragma unroll
    for (int jj = 0; jj < 8; jj++)
      stsm4(stg + frag(jj, 8192), pack_bf16(d[8 * jj] * s0, d[8 * jj + 1] * s0), pack_bf16(d[8 * jj + 2] * s1, d[8 * jj + 3] * s1),
            pack_bf16(d[8 * jj + 4] * s0, d[8 * jj + 5] * s0), pack_bf16(d[8 * jj + 6] * s1, d[8 * jj + 7] * s1));
    fence_async_smem();
    mbar_arrive(stg_full);
    stg_phase ^= 1;
  }
};

constexpr float SM_SCALE = 0.08838834764831845f * 1.4426950408889634f;

struct Attn {
  float o[64], s[64];
  uint32_t p[32], q[32];
  float m0, m1, l0, l1;
};

__device__ __forceinline__ void issue_qk(Attn& A, uint32_t kaddr) {
  const uint64_t d = desc_k(kaddr);
#pragma unroll
  for (int kk = 0; kk < 8; kk++)
    wgmma_rs_n128<0>(A.s, A.q[4 * kk], A.q[4 * kk + 1], A.q[4 * kk + 2], A.q[4 * kk + 3], d + (((kk >> 2) * HALF + (kk & 3) * 32) >> 4), kk > 0);
  wg_commit();
}
__device__ __forceinline__ void issue_pv(Attn& A, uint32_t vaddr, int acc) {
  const uint64_t d = desc_mn(vaddr);
#pragma unroll
  for (int kk = 0; kk < 8; kk++)
    wgmma_rs_n128<1>(A.o, A.p[4 * kk], A.p[4 * kk + 1], A.p[4 * kk + 2], A.p[4 * kk + 3], d + ((kk * 2048) >> 4), kk > 0 ? 1 : acc);
  wg_commit();
}
__device__ __forceinline__ void pack_p(Attn& A) {
#pragma unroll
  for (int i = 0; i < 32; i++) A.p[i] = pack_bf16(A.s[2 * i], A.s[2 * i + 1]);
}
template <bool FIRST> __device__ __forceinline__ void softmax(Attn& A, float& c0, float& c1) {
  float x0 = fmaxf(A.s[0], A.s[1]), x1 = fmaxf(A.s[2], A.s[3]);
  float y0 = fmaxf(A.s[4], A.s[5]), y1 = fmaxf(A.s[6], A.s[7]);
#pragma unroll
  for (int j = 2; j < 16; j += 2) {
    x0 = fmaxf(x0, fmaxf(A.s[4 * j], A.s[4 * j + 1])); x1 = fmaxf(x1, fmaxf(A.s[4 * j + 2], A.s[4 * j + 3]));
    y0 = fmaxf(y0, fmaxf(A.s[4 * j + 4], A.s[4 * j + 5])); y1 = fmaxf(y1, fmaxf(A.s[4 * j + 6], A.s[4 * j + 7]));
  }
  x0 = fmaxf(x0, y0); x1 = fmaxf(x1, y1);
  if (!FIRST) { x0 = fmaxf(x0, A.m0); x1 = fmaxf(x1, A.m1); }
  x0 = fmaxf(x0, __shfl_xor_sync(~0u, x0, 1)); x1 = fmaxf(x1, __shfl_xor_sync(~0u, x1, 1));
  x0 = fmaxf(x0, __shfl_xor_sync(~0u, x0, 2)); x1 = fmaxf(x1, __shfl_xor_sync(~0u, x1, 2));
  const float n0 = -x0 * SM_SCALE, n1 = -x1 * SM_SCALE;
  if (!FIRST) { c0 = ex2((A.m0 - x0) * SM_SCALE); c1 = ex2((A.m1 - x1) * SM_SCALE); }
  A.m0 = x0; A.m1 = x1;
  float a0 = 0.f, a1 = 0.f, b0 = 0.f, b1 = 0.f;
#pragma unroll
  for (int j = 0; j < 16; j++) {
    A.s[4 * j] = ex2(fmaf(A.s[4 * j], SM_SCALE, n0)); A.s[4 * j + 1] = ex2(fmaf(A.s[4 * j + 1], SM_SCALE, n0));
    A.s[4 * j + 2] = ex2(fmaf(A.s[4 * j + 2], SM_SCALE, n1)); A.s[4 * j + 3] = ex2(fmaf(A.s[4 * j + 3], SM_SCALE, n1));
    a0 += A.s[4 * j]; b0 += A.s[4 * j + 1]; a1 += A.s[4 * j + 2]; b1 += A.s[4 * j + 3];
  }
  if (FIRST) { A.l0 = a0 + b0; A.l1 = a1 + b1; }
  else { A.l0 = fmaf(A.l0, c0, a0 + b0); A.l1 = fmaf(A.l1, c1, a1 + b1); }
}
__device__ __forceinline__ void causal_mask(Attn& A, int rel) {
#pragma unroll
  for (int j = 0; j < 16; j++) {
    if (8 * j > rel) A.s[4 * j] = -INFINITY;
    if (8 * j + 1 > rel) A.s[4 * j + 1] = -INFINITY;
    if (8 * j > rel + 8) A.s[4 * j + 2] = -INFINITY;
    if (8 * j + 1 > rel + 8) A.s[4 * j + 3] = -INFINITY;
  }
}
__device__ __forceinline__ void finish_item(Ctx& C, Attn& A, float l0, float l1) {
  l0 += __shfl_xor_sync(~0u, l0, 1); l1 += __shfl_xor_sync(~0u, l1, 1);
  l0 += __shfl_xor_sync(~0u, l0, 2); l1 += __shfl_xor_sync(~0u, l1, 2);
  C.stage_out(A.o, 1.f / l0, 1.f / l1);
}
template <bool HAS_PREV> __device__ __forceinline__ void item_begin(Ctx& C, Attn& A, Cur& cur, bool skip, int pv_acc, int rel) {
  const Cur cq = cur; cur.adv();
  Cur ck = cur, cv = cur, cs = cur; cur.adv();
  if (HAS_PREV) { cv = cur; cur.adv(); }
  C.wait(cq);
  {
    const uint32_t qa = C.addr(cq) + C.w * 8192;
#pragma unroll
    for (int jj = 0; jj < 8; jj++) ldsm4(qa + C.frag(jj, HALF), A.q[4 * jj], A.q[4 * jj + 1], A.q[4 * jj + 2], A.q[4 * jj + 3]);
  }
  if (skip) { C.wait(ck); C.release(ck); ck = cur; cur.adv(); cs = cur; cur.adv(); }
  C.wait(ck);
  C.turn_begin();
  wg_fence();
  issue_qk(A, C.addr(ck));
  if (HAS_PREV) { C.wait(cv); issue_pv(A, C.addr(cv), pv_acc); }
  C.turn_end();
  if (HAS_PREV) wg_wait<1>(); else wg_wait<0>();
  reg_fence(A.s);
  C.release(cq); C.release(ck);
  const float pl0 = A.l0, pl1 = A.l1;
  float c0, c1;
  causal_mask(A, rel);
  softmax<true>(A, c0, c1);
  if (HAS_PREV) {
    wg_wait<0>();
    reg_fence(A.o);
    C.release(cv);
    finish_item(C, A, pl0, pl1);
  }
  pack_p(A);
  if (skip) { C.wait(cs); C.release(cs); }
}
__device__ __forceinline__ void item_step(Ctx& C, Attn& A, Cur& cur, int pv_acc) {
  const Cur ck = cur; cur.adv();
  const Cur cv = cur; cur.adv();
  C.wait(ck);
  C.turn_begin();
  wg_fence();
  issue_qk(A, C.addr(ck));
  C.wait(cv);
  issue_pv(A, C.addr(cv), pv_acc);
  C.turn_end();
  wg_wait<1>();
  reg_fence(A.s);
  C.release(ck);
  float c0, c1;
  softmax<false>(A, c0, c1);
  wg_wait<0>();
  reg_fence(A.o);
  C.release(cv);
#pragma unroll
  for (int j = 0; j < 16; j++) { A.o[4 * j] *= c0; A.o[4 * j + 1] *= c0; A.o[4 * j + 2] *= c1; A.o[4 * j + 3] *= c1; }
  pack_p(A);
}

template <bool LOAD_A> __device__ __forceinline__ void proj_unit(Ctx& C, Cur& cur, uint32_t (&a)[128], float (&acc)[64]) {
#pragma unroll
  for (int i = 0; i < 4; i++) {
    Cur ca = cur;
    if (LOAD_A) {
      cur.adv();
      C.wait(ca);
      const uint32_t aa = C.addr(ca) + C.w * 8192;
#pragma unroll
      for (int jj = 0; jj < 8; jj++) ldsm4(aa + C.frag(jj, HALF), a[32 * i + 4 * jj], a[32 * i + 4 * jj + 1], a[32 * i + 4 * jj + 2], a[32 * i + 4 * jj + 3]);
    }
    const Cur cb = cur; cur.adv();
    C.wait(cb);
    C.turn_begin();
    wg_fence();
    const uint64_t d = desc_mn(C.addr(cb));
#pragma unroll
    for (int kk = 0; kk < 8; kk++)
      wgmma_rs_n128<1>(acc, a[32 * i + 4 * kk], a[32 * i + 4 * kk + 1], a[32 * i + 4 * kk + 2], a[32 * i + 4 * kk + 3], d + ((kk * 2048) >> 4), (i | kk) > 0);
    wg_commit();
    C.turn_end();
    wg_wait<0>();
    reg_fence(acc);
    if (LOAD_A) C.release(ca);
    C.release(cb);
  }
  C.stage_out(acc, 1.f, 1.f);
}

__global__ void __cluster_dims__(2, 1, 1) __launch_bounds__(384, 1) fused_kernel(const __grid_constant__ Params P) {
  extern __shared__ uint8_t smem_raw[];
  uint8_t* smem = smem_raw + ((1024 - (smem_u32(smem_raw) & 1023)) & 1023);
  const int tid = threadIdx.x;
  const int c = blockIdx.x >> 1, r = blockIdx.x & 1;
  const unsigned ep = g_epoch[blockIdx.x] + 1;
  if (c >= 64) {
    moe_cta(P, blockIdx.x - 128, ep, smem);
    if (tid == 0) g_epoch[blockIdx.x] = ep;
    return;
  }
  const uint32_t sb = smem_u32(smem);
  const uint32_t full0 = sb + SMEM_BAR, empty0 = full0 + 8 * NSLOT, stgf0 = empty0 + 8 * NSLOT, stge0 = stgf0 + 16;
  if (tid == 0) {
    for (int i = 0; i < NSLOT; i++) { mbar_init(full0 + 8 * i, 1); mbar_init(empty0 + 8 * i, 4); }
    for (int i = 0; i < 2; i++) { mbar_init(stgf0 + 8 * i, 128); mbar_init(stge0 + 8 * i, 1); }
    asm volatile("fence.mbarrier_init.release.cluster;" ::: "memory");
  }
  asm volatile("barrier.cluster.arrive.aligned;\nbarrier.cluster.wait.aligned;" ::: "memory");

  const int rp = c & 7, g = c >> 3;
  const int rb = 2 * rp + r;
  const int ma = rp & 3, hb = rp >> 2;
  const int j3 = c & 15, ks = c >> 5, ncol = 2 * ((c >> 4) & 1) + r;
  const int wg = __shfl_sync(~0u, tid >> 7, 0);

  if (wg == 0) {
    asm volatile("setmaxnreg.dec.sync.aligned.u32 40;");
    const int warp = tid >> 5;
    if (warp == 0) {
      if (tid == 0) {
        Cur cur{0, 0};
        uint32_t dst, bar;
        auto acquire = [&]() {
          mbar_wait(empty0 + 8 * cur.slot, cur.phase ^ 1);
          dst = sb + cur.slot * TILE; bar = full0 + 8 * cur.slot;
          mbar_expect(bar, TILE);
          cur.adv();
        };
        for (int u = 0; u < 12; u++) {
          const CUtensorMap* wm = u >= 8 ? &P.wq : ((u & 1) ? &P.wuv : &P.wuk);
          const CUtensorMap* am = u >= 8 ? &P.xn : &P.ckv;
          const int head = 4 * g + (u >= 8 ? u - 8 : u >> 1);
          if (u == 8) { flag_wait(F_LN + rb, ep * 8); fence_async_all(); }
          for (int i = 0; i < 4; i++) {
            if ((u & 7) == 0) {
              acquire();
              tma_load(dst, am, 128 * i, rb * 128, bar);
              tma_load(dst + HALF, am, 128 * i + 64, rb * 128, bar);
            }
            acquire();
            tma_load_mc(dst + r * HALF, wm, head * 128 + 64 * r, 128 * i, bar);
          }
        }
        const uint8_t* prev_v = nullptr;
        for (int it = 0; it < 4; it++) {
          const int head = 4 * g + (it & 2) + hb;
          const int m = (it & 1) ? 7 - ma : ma;
          const int j = 2 * m + (r ^ (it & 1));
          if (!(it & 1)) { flag_wait(F_HEAD + head, ep * 96); fence_async_all(); }
          acquire();
          bulk_load(dst, g_qkv + (size_t)(head * 16 + j) * TILE, TILE, bar);
          for (int b = 2 * m + 1; b >= 0; b--) {
            acquire();
            bulk_load_mc(dst + r * HALF, g_qkv + (size_t)((NH + head) * 16 + b) * TILE + r * HALF, HALF, bar);
            if (prev_v) { acquire(); bulk_load_mc(dst + r * HALF, prev_v, HALF, bar); }
            prev_v = g_qkv + (size_t)((2 * NH + head) * 16 + b) * TILE + r * HALF;
          }
        }
        acquire(); bulk_load_mc(dst + r * HALF, prev_v, HALF, bar);
        for (int t = 0; t < 16; t++) {
          const int head = 16 * ks + 4 * ((t & 7) >> 1) + 2 * (t >> 3) + (t & 1);
          acquire();
          tma_load(dst + ks * HALF, &P.wo, ncol * 128, head * 128, bar);
          tma_load(dst + (ks ^ 1) * HALF, &P.wo, ncol * 128 + 64, head * 128, bar);
          if ((t & 7) == 0) { flag_wait(F_CTX + j3 * 4 + ks * 2 + (t >> 3), ep * 16); fence_async_all(); }
          acquire();
          bulk_load_mc(dst + r * HALF, g_ctx + (size_t)(head * 16 + j3) * TILE + r * HALF, HALF, bar);
        }
        flag_wait(F_LN + j3, ep * 8);
        flag_wait(F_MOE, ep * 4);
        fence_async_all();
        acquire();
        tma_load(dst, &P.x, ncol * 128 + 64 * ks, j3 * 128, bar);
        tma_load(dst + HALF, &P.xn, ncol * 128 + 64 * ks, j3 * 128, bar);
        for (int i = 0; i < NSLOT; i++) { mbar_wait(empty0 + 8 * cur.slot, cur.phase ^ 1); cur.adv(); }
        g_epoch[blockIdx.x] = ep;
      }
    } else if (warp < 3) {
      if ((tid & 31) == 0) {
        const int w = warp - 1;
        const uint32_t stg = sb + SMEM_STG + w * HALF;
        for (int job = 0; job < 17; job++) {
          mbar_wait(stgf0 + 8 * w, job & 1);
          int flag = -1;
          if (job < 16) {
            uint8_t* d;
            if (job < 12) {
              const int head = 4 * g + (job >= 8 ? job - 8 : job >> 1);
              const int kind = job >= 8 ? 0 : 1 + (job & 1);
              d = g_qkv + (size_t)((kind * NH + head) * 16 + rb) * TILE;
              flag = F_HEAD + head;
            } else {
              const int it = job - 12;
              const int head = 4 * g + (it & 2) + hb;
              const int m = (it & 1) ? 7 - ma : ma;
              const int j = 2 * m + (r ^ (it & 1));
              d = g_ctx + (size_t)(head * 16 + j) * TILE;
              flag = F_CTX + j * 4 + (g >> 2) * 2 + (it >> 1);
            }
            bulk_store(d + w * 8192, stg, 8192);
            bulk_store(d + HALF + w * 8192, stg + 8192, 8192);
          } else {
            tma_store(&P.out, ncol * 128 + 64 * ks, j3 * 128 + 64 * w, stg);
          }
          asm volatile("cp.async.bulk.commit_group;" ::: "memory");
          asm volatile("cp.async.bulk.wait_group.read 0;" ::: "memory");
          mbar_arrive(stge0 + 8 * w);
          asm volatile("cp.async.bulk.wait_group 0;" ::: "memory");
          if (flag >= 0) { fence_async_all(); flag_add(flag); }
        }
      }
    } else {
      bar_sync(3, 288);
      if (tid == 96) { __threadfence(); fence_async_all(); flag_add(F_LN + rb); }
    }
  } else {
    asm volatile("setmaxnreg.inc.sync.aligned.u32 232;");
    const int t = tid & 127, lane = tid & 31, wi = t >> 5;
    Ctx C;
    C.sb = sb; C.full0 = full0; C.w = wg - 1;
    asm("mapa.shared::cluster.u32 %0, %1, %2;" : "=r"(C.rel) : "r"(empty0), "r"(wi & 1));
    C.rel_pred = lane == 0 && wi < 2;
    C.stg = sb + SMEM_STG + C.w * HALF;
    C.stg_full = stgf0 + 8 * C.w; C.stg_empty = stge0 + 8 * C.w; C.stg_phase = 0;
    C.frag_off = (16 * wi + (lane & 15)) * 128;
    C.frag_x = ((lane >> 4) ^ (lane & 7)) * 16;
    TL(C.w * 16 + 0);
    {
      const int row = rb * 128 + 16 * g + 2 * (4 * C.w + wi);
      const uint4* px = (const uint4*)(P.px + (size_t)row * DM);
      const uint4 a0 = __ldg(px + lane), b0 = __ldg(px + 32 + lane), a1 = __ldg(px + 64 + lane), b1 = __ldg(px + 96 + lane);
      const uint4 wa = __ldg((const uint4*)P.w_r + lane), wb = __ldg((const uint4*)P.w_r + 32 + lane);
      ln_row(a0, b0, wa, wb, row, lane);
      ln_row(a1, b1, wa, wb, row + 1, lane);
      bar_arrive(3, 288);
    }
    if (C.w == 1) bar_arrive(1, 256);
    Cur cur{0, 0};
    TL(C.w * 16 + 1);
    {
      uint32_t a[128];
      float acc[64];
#pragma unroll 1
      for (int half = 0; half < 2; half++) {
        proj_unit<true>(C, cur, a, acc);
        if (half == 0) TL(C.w * 16 + 2);
#pragma unroll 1
        for (int u = half ? 5 : 1; u < 8; u++) proj_unit<false>(C, cur, a, acc);
      }
    }
    TL(C.w * 16 + 3);
    {
      Attn A;
      const int rel = 64 * C.w + 16 * wi + (lane >> 2) - 2 * (lane & 3);
      A.l0 = A.l1 = 0.f;
      int pv_acc = 0;
#pragma unroll 1
      for (int it = 0; it < 4; it++) {
        const int m = (it & 1) ? 7 - ma : ma;
        const int role = r ^ (it & 1);
        if (it == 0) item_begin<false>(C, A, cur, role == 0, 0, rel);
        else item_begin<true>(C, A, cur, role == 0, pv_acc, rel);
        pv_acc = 0;
#pragma unroll 1
        for (int b = 2 * m + role; b > 0; b--) { item_step(C, A, cur, pv_acc); pv_acc = 1; }
        TL(C.w * 16 + 4 + it);
      }
      const Cur cv = cur; cur.adv();
      C.wait(cv);
      C.turn_begin();
      wg_fence();
      issue_pv(A, C.addr(cv), pv_acc);
      C.turn_end();
      wg_wait<0>();
      reg_fence(A.o);
      C.release(cv);
      finish_item(C, A, A.l0, A.l1);
      if (C.w == 0) C.turn_begin();
    }
    TL(C.w * 16 + 8);
    {
      float acc[64];
      Cur pb = cur, pa = cur;
#pragma unroll 1
      for (int h = 0; h < 16; h++) {
        const Cur cb = cur; cur.adv();
        const Cur ca = cur; cur.adv();
        C.wait(cb); C.wait(ca);
        wg_fence();
        const uint64_t da = desc_k(C.addr(ca) + C.w * 8192), db = desc_mn(C.addr(cb));
#pragma unroll
        for (int kk = 0; kk < 8; kk++)
          wgmma_ss_n128<1>(acc, da + (((kk >> 2) * HALF + (kk & 3) * 32) >> 4), db + ((kk * 2048) >> 4), kk > 0 ? 1 : h);
        wg_commit();
        wg_wait<1>();
        if (h > 0) { C.release(pb); C.release(pa); }
        pb = cb; pa = ca;
      }
      wg_wait<0>();
      reg_fence(acc);
      C.release(pb); C.release(pa);
      TL(C.w * 16 + 9);
      float4* mine = g_part + (size_t)blockIdx.x * 2048 + C.w * 1024 + t;
      const float4* theirs = g_part + (size_t)(blockIdx.x ^ 64) * 2048 + C.w * 1024 + t;
#pragma unroll
      for (int i = 0; i < 8; i++) __stcg(mine + i * 128, make_float4(acc[32 + 4 * i], acc[33 + 4 * i], acc[34 + 4 * i], acc[35 + 4 * i]));
      bar_sync(4 + C.w, 128);
      if (t == 0) {
        __threadfence();
        flag_add(F_PART + blockIdx.x * 2 + C.w);
        flag_wait(F_PART + (blockIdx.x ^ 64) * 2 + C.w, ep);
      }
      const Cur cr = cur;
      C.wait(cr);
      uint32_t xr[16], nr[16];
      const uint32_t xa = C.addr(cr) + C.w * 8192;
#pragma unroll
      for (int jj = 0; jj < 4; jj++) {
        ldsm4(xa + C.frag(jj, 0), xr[4 * jj], xr[4 * jj + 1], xr[4 * jj + 2], xr[4 * jj + 3]);
        ldsm4(xa + HALF + C.frag(jj, 0), nr[4 * jj], nr[4 * jj + 1], nr[4 * jj + 2], nr[4 * jj + 3]);
      }
      const int sel = __ldcg(&g_sel);
      const int row0 = j3 * 128 + 64 * C.w + 16 * wi + (lane >> 2);
      if (sel == row0 || sel == row0 + 8) {
        const float gate = __ldcg(&g_gate);
        const float* yp = g_ypart + ncol * 128 + 64 * ks + 2 * (lane & 3);
#pragma unroll
        for (int j = 0; j < 8; j++) {
          float y0 = 0.f, y1 = 0.f;
#pragma unroll
          for (int q = 0; q < 4; q++) { y0 += __ldcg(yp + q * DM + 8 * j); y1 += __ldcg(yp + q * DM + 8 * j + 1); }
          y0 = rbf(rbf(y0) * gate); y1 = rbf(rbf(y1) * gate);
          if (sel == row0) nr[2 * j] = pack_bf16(bf_lo(nr[2 * j]) + y0, bf_hi(nr[2 * j]) + y1);
          else nr[2 * j + 1] = pack_bf16(bf_lo(nr[2 * j + 1]) + y0, bf_hi(nr[2 * j + 1]) + y1);
        }
      }
      bar_sync(4 + C.w, 128);
      C.release(cr);
      TL(C.w * 16 + 10);
#pragma unroll
      for (int i = 0; i < 8; i++) {
        const float4 v = __ldcg(theirs + i * 128);
        acc[4 * i] += v.x; acc[4 * i + 1] += v.y; acc[4 * i + 2] += v.z; acc[4 * i + 3] += v.w;
      }
      uint32_t o[16];
#pragma unroll
      for (int i = 0; i < 16; i++)
        o[i] = pack_bf16(rbf(bf_lo(xr[i]) + rbf(acc[2 * i])) + bf_lo(nr[i]), rbf(bf_hi(xr[i]) + rbf(acc[2 * i + 1])) + bf_hi(nr[i]));
      mbar_wait(C.stg_empty, C.stg_phase ^ 1);
#pragma unroll
      for (int jj = 0; jj < 4; jj++) stsm4(C.stg + C.frag(jj, 0), o[4 * jj], o[4 * jj + 1], o[4 * jj + 2], o[4 * jj + 3]);
      fence_async_smem();
      mbar_arrive(C.stg_full);
      TL(C.w * 16 + 11);
    }
  }
}

typedef CUresult (*EncodeFn)(CUtensorMap*, CUtensorMapDataType, cuuint32_t, void*, const cuuint64_t*, const cuuint64_t*,
                             const cuuint32_t*, const cuuint32_t*, CUtensorMapInterleave, CUtensorMapSwizzle,
                             CUtensorMapL2promotion, CUtensorMapFloatOOBfill);

void make_map(EncodeFn fn, CUtensorMap* m, const void* ptr, uint64_t cols, uint64_t rows, uint32_t box_rows) {
  cuuint64_t dims[2] = {cols, rows};
  cuuint64_t strides[1] = {cols * 2};
  cuuint32_t box[2] = {64, box_rows};
  cuuint32_t es[2] = {1, 1};
  fn(m, CU_TENSOR_MAP_DATA_TYPE_BFLOAT16, 2, const_cast<void*>(ptr), dims, strides, box, es, CU_TENSOR_MAP_INTERLEAVE_NONE,
     CU_TENSOR_MAP_SWIZZLE_128B, CU_TENSOR_MAP_L2_PROMOTION_L2_128B, CU_TENSOR_MAP_FLOAT_OOB_FILL_NONE);
}

}

extern "C" void kernel_launch(void* const* d_in, const int* in_sizes, int n_in, void* d_out, int out_size) {
  static EncodeFn fn = nullptr;
  static void* xn_ptr = nullptr;
  if (!fn) {
    void* f = nullptr;
    cudaDriverEntryPointQueryResult qr;
    cudaGetDriverEntryPoint("cuTensorMapEncodeTiled", &f, cudaEnableDefault, &qr);
    fn = (EncodeFn)f;
    cudaGetSymbolAddress(&xn_ptr, g_xn);
    cudaFuncSetAttribute(fused_kernel, cudaFuncAttributeMaxDynamicSharedMemorySize, SMEM_TOTAL);
  }
  Params P;
  make_map(fn, &P.x, d_in[0], DM, SEQ, 128);
  make_map(fn, &P.ckv, d_in[1], DM, SEQ, 128);
  make_map(fn, &P.xn, xn_ptr, DM, SEQ, 128);
  make_map(fn, &P.wq, d_in[2], NH * 128, DM, 128);
  make_map(fn, &P.wuk, d_in[3], NH * 128, DM, 128);
  make_map(fn, &P.wuv, d_in[4], NH * 128, DM, 128);
  make_map(fn, &P.wo, d_in[5], DM, NH * 128, 128);
  make_map(fn, &P.out, d_out, DM, SEQ, 64);
  P.px = (const __nv_bfloat16*)d_in[0];
  P.w_r = (const __nv_bfloat16*)d_in[7];
  P.w_gate = (const __nv_bfloat16*)d_in[8];
  P.w_up = (const __nv_bfloat16*)d_in[9];
  P.w_down = (const __nv_bfloat16*)d_in[10];
  fused_kernel<<<NCTA, 384, SMEM_TOTAL>>>(P);
}
```

```cpp
#include <cuda_runtime.h>
#include <cuda_bf16.h>
#include <cuda.h>
#include <stdint.h>

namespace {

constexpr int SEQ = 2048, DM = 512, NH = 32, FF = 1376;
constexpr int NSLOT = 6;
constexpr int TILE = 32768;
constexpr int HALF = 16384;
constexpr int SMEM_STG = NSLOT * TILE;
constexpr int SMEM_BAR = SMEM_STG + 32768;
constexpr int SMEM_TOTAL = SMEM_BAR + 256 + 1024;
constexpr int NCTA = 132;
constexpr int SPIN_LIMIT = 1 << 22;

constexpr int F_LN = 0;
constexpr int F_HEAD = 16;
constexpr int F_CTX = 48;
constexpr int F_PART = 112;
constexpr int F_MOE = 368;
constexpr int F_COUNT = 369;

__device__ __align__(1024) __nv_bfloat16 g_xn[SEQ * DM];
__device__ float g_r[SEQ];
__device__ __align__(1024) uint8_t g_qkv[3ull * NH * 16 * TILE];
__device__ __align__(1024) uint8_t g_ctx[1ull * NH * 16 * TILE];
__device__ __align__(1024) float4 g_part[128 * 256 * 8];
__device__ float g_ypart[4 * DM];
__device__ int g_sel;
__device__ float g_gate;
__device__ unsigned g_flags[F_COUNT * 32];
__device__ unsigned g_epoch[NCTA];
#define TL(i)

__device__ __forceinline__ uint32_t smem_u32(const void* p) { return (uint32_t)__cvta_generic_to_shared(p); }
__device__ __forceinline__ void mbar_init(uint32_t bar, int cnt) { asm volatile("mbarrier.init.shared::cta.b64 [%0], %1;" :: "r"(bar), "r"(cnt)); }
__device__ __forceinline__ void mbar_arrive(uint32_t bar) { asm volatile("mbarrier.arrive.shared::cta.b64 _, [%0];" :: "r"(bar) : "memory"); }
__device__ __forceinline__ void mbar_arrive_cluster_if(uint32_t bar, bool pred) {
  asm volatile("{\n.reg .pred p;\nsetp.ne.b32 p, %1, 0;\n@p mbarrier.arrive.shared::cluster.b64 _, [%0];\n}" :: "r"(bar), "r"((int)pred) : "memory");
}
__device__ __forceinline__ void mbar_expect(uint32_t bar, int bytes) { asm volatile("mbarrier.arrive.expect_tx.shared::cta.b64 _, [%0], %1;" :: "r"(bar), "r"(bytes) : "memory"); }
__device__ __forceinline__ void mbar_wait(uint32_t bar, uint32_t parity) {
  asm volatile("{\n.reg .pred p, q;\n.reg .b32 n;\n"
               "mbarrier.try_wait.parity.shared::cta.b64 p, [%0], %1;\n@p bra DONE;\nmov.b32 n, 0;\n"
               "LOOP:\nmbarrier.try_wait.parity.shared::cta.b64 p, [%0], %1;\nadd.s32 n, n, 1;\nsetp.lt.s32 q, n, %2;\n@p bra DONE;\n@q bra LOOP;\n"
               "DONE:\n}" :: "r"(bar), "r"(parity), "n"(SPIN_LIMIT) : "memory");
}
__device__ __forceinline__ void bulk_load(uint32_t dst, const void* src, int bytes, uint32_t bar) {
  asm volatile("cp.async.bulk.shared::cluster.global.mbarrier::complete_tx::bytes [%0], [%1], %2, [%3];" :: "r"(dst), "l"(src), "r"(bytes), "r"(bar) : "memory");
}
__device__ __forceinline__ void bulk_load_mc(uint32_t dst, const void* src, int bytes, uint32_t bar) {
  asm volatile("cp.async.bulk.shared::cluster.global.mbarrier::complete_tx::bytes.multicast::cluster [%0], [%1], %2, [%3], %4;" :: "r"(dst), "l"(src), "r"(bytes), "r"(bar), "h"((uint16_t)3) : "memory");
}
__device__ __forceinline__ void tma_load(uint32_t dst, const CUtensorMap* map, int c0, int c1, uint32_t bar) {
  asm volatile("cp.async.bulk.tensor.2d.shared::cluster.global.mbarrier::complete_tx::bytes [%0], [%1, {%3, %4}], [%2];" :: "r"(dst), "l"(map), "r"(bar), "r"(c0), "r"(c1) : "memory");
}
__device__ __forceinline__ void tma_load_mc(uint32_t dst, const CUtensorMap* map, int c0, int c1, uint32_t bar) {
  asm volatile("cp.async.bulk.tensor.2d.shared::cluster.global.mbarrier::complete_tx::bytes.multicast::cluster [%0], [%1, {%3, %4}], [%2], %5;" :: "r"(dst), "l"(map), "r"(bar), "r"(c0), "r"(c1), "h"((uint16_t)3) : "memory");
}
__device__ __forceinline__ void bulk_store(void* dst, uint32_t src, int bytes) {
  asm volatile("cp.async.bulk.global.shared::cta.bulk_group [%0], [%1], %2;" :: "l"(dst), "r"(src), "r"(bytes) : "memory");
}
__device__ __forceinline__ void tma_store(const CUtensorMap* map, int c0, int c1, uint32_t src) {
  asm volatile("cp.async.bulk.tensor.2d.global.shared::cta.bulk_group [%0, {%2, %3}], [%1];" :: "l"(map), "r"(src), "r"(c0), "r"(c1) : "memory");
}
__device__ __forceinline__ void fence_async_smem() { asm volatile("fence.proxy.async.shared::cta;" ::: "memory"); }
__device__ __forceinline__ void fence_async_all() { asm volatile("fence.proxy.async;" ::: "memory"); }
__device__ __forceinline__ void flag_add(int f) { asm volatile("red.release.gpu.global.add.u32 [%0], 1;" :: "l"(&g_flags[f * 32]) : "memory"); }
__device__ __forceinline__ void flag_wait(int f, unsigned target) {
  const unsigned* p = &g_flags[f * 32];
  for (int n = 0; n < SPIN_LIMIT; ++n) {
    unsigned v;
    asm volatile("ld.acquire.gpu.global.u32 %0, [%1];" : "=r"(v) : "l"(p) : "memory");
    if ((int)(v - target) >= 0) break;
  }
}
__device__ __forceinline__ void bar_sync(int id, int n) { asm volatile("bar.sync %0, %1;" :: "r"(id), "r"(n) : "memory"); }
__device__ __forceinline__ void bar_arrive(int id, int n) { asm volatile("bar.arrive %0, %1;" :: "r"(id), "r"(n) : "memory"); }
__device__ __forceinline__ void wg_fence() { asm volatile("wgmma.fence.sync.aligned;" ::: "memory"); }
__device__ __forceinline__ void wg_commit() { asm volatile("wgmma.commit_group.sync.aligned;" ::: "memory"); }
template <int N> __device__ __forceinline__ void wg_wait() { asm volatile("wgmma.wait_group.sync.aligned %0;" :: "n"(N) : "memory"); }
template <int N> __device__ __forceinline__ void reg_fence(float (&d)[N]) {
#pragma unroll
  for (int i = 0; i < N; i++) asm volatile("" : "+f"(d[i]) :: "memory");
}
__device__ __forceinline__ void ldsm4(uint32_t addr, uint32_t& r0, uint32_t& r1, uint32_t& r2, uint32_t& r3) {
  asm volatile("ldmatrix.sync.aligned.m8n8.x4.shared.b16 {%0, %1, %2, %3}, [%4];" : "=r"(r0), "=r"(r1), "=r"(r2), "=r"(r3) : "r"(addr) : "memory");
}
__device__ __forceinline__ void stsm4(uint32_t addr, uint32_t r0, uint32_t r1, uint32_t r2, uint32_t r3) {
  asm volatile("stmatrix.sync.aligned.m8n8.x4.shared.b16 [%0], {%1, %2, %3, %4};" :: "r"(addr), "r"(r0), "r"(r1), "r"(r2), "r"(r3) : "memory");
}
__device__ __forceinline__ uint32_t pack_bf16(float lo, float hi) {
  uint32_t r; asm("cvt.rn.bf16x2.f32 %0, %1, %2;" : "=r"(r) : "f"(hi), "f"(lo)); return r;
}
__device__ __forceinline__ float ex2(float x) { float y; asm("ex2.approx.ftz.f32 %0, %1;" : "=f"(y) : "f"(x)); return y; }
__device__ __forceinline__ float bf_lo(uint32_t v) { return __uint_as_float(v << 16); }
__device__ __forceinline__ float bf_hi(uint32_t v) { return __uint_as_float(v & 0xffff0000u); }
__device__ __forceinline__ float rbf(float x) { return __bfloat162float(__float2bfloat16_rn(x)); }

__device__ __forceinline__ uint32_t desc_lo(uint32_t addr) { return ((addr & 0x3FFFF) >> 4) | ((uint32_t)(HALF >> 4) << 16); }
__device__ __forceinline__ uint64_t desc(uint32_t lo) { return (uint64_t)lo | ((uint64_t)(64u | (1u << 30)) << 32); }

template<int TB> __device__ __forceinline__ void wgmma_ss_n128(float (&d)[64], uint64_t descA, uint64_t descB, int scaleD) {
  asm volatile("{\n.reg .pred p;\nsetp.ne.b32 p, %66, 0;\n"
    "wgmma.mma_async.sync.aligned.m64n128k16.f32.bf16.bf16 "
    "{%0, %1, %2, %3, %4, %5, %6, %7, %8, %9, %10, %11, %12, %13, %14, %15, "
    "%16, %17, %18, %19, %20, %21, %22, %23, %24, %25, %26, %27, %28, %29, %30, %31, "
    "%32, %33, %34, %35, %36, %37, %38, %39, %40, %41, %42, %43, %44, %45, %46, %47, "
    "%48, %49, %50, %51, %52, %53, %54, %55, %56, %57, %58, %59, %60, %61, %62, %63}, "
    "%64, %65, p, 1, 1, 0, %67;\n}\n"
    : "+f"(d[0]), "+f"(d[1]), "+f"(d[2]), "+f"(d[3]), "+f"(d[4]), "+f"(d[5]), "+f"(d[6]), "+f"(d[7]),
      "+f"(d[8]), "+f"(d[9]), "+f"(d[10]), "+f"(d[11]), "+f"(d[12]), "+f"(d[13]), "+f"(d[14]), "+f"(d[15]),
      "+f"(d[16]), "+f"(d[17]), "+f"(d[18]), "+f"(d[19]), "+f"(d[20]), "+f"(d[21]), "+f"(d[22]), "+f"(d[23]),
      "+f"(d[24]), "+f"(d[25]), "+f"(d[26]), "+f"(d[27]), "+f"(d[28]), "+f"(d[29]), "+f"(d[30]), "+f"(d[31]),
      "+f"(d[32]), "+f"(d[33]), "+f"(d[34]), "+f"(d[35]), "+f"(d[36]), "+f"(d[37]), "+f"(d[38]), "+f"(d[39]),
      "+f"(d[40]), "+f"(d[41]), "+f"(d[42]), "+f"(d[43]), "+f"(d[44]), "+f"(d[45]), "+f"(d[46]), "+f"(d[47]),
      "+f"(d[48]), "+f"(d[49]), "+f"(d[50]), "+f"(d[51]), "+f"(d[52]), "+f"(d[53]), "+f"(d[54]), "+f"(d[55]),
      "+f"(d[56]), "+f"(d[57]), "+f"(d[58]), "+f"(d[59]), "+f"(d[60]), "+f"(d[61]), "+f"(d[62]), "+f"(d[63])
    : "l"(descA), "l"(descB), "r"(scaleD), "n"(TB));
}

template<int TB> __device__ __forceinline__ void wgmma_rs_n128(float (&d)[64], uint32_t a0, uint32_t a1, uint32_t a2, uint32_t a3, uint64_t descB, int scaleD) {
  asm volatile("{\n.reg .pred p;\nsetp.ne.b32 p, %69, 0;\n"
    "wgmma.mma_async.sync.aligned.m64n128k16.f32.bf16.bf16 "
    "{%0, %1, %2, %3, %4, %5, %6, %7, %8, %9, %10, %11, %12, %13, %14, %15, "
    "%16, %17, %18, %19, %20, %21, %22, %23, %24, %25, %26, %27, %28, %29, %30, %31, "
    "%32, %33, %34, %35, %36, %37, %38, %39, %40, %41, %42, %43, %44, %45, %46, %47, "
    "%48, %49, %50, %51, %52, %53, %54, %55, %56, %57, %58, %59, %60, %61, %62, %63}, "
    "{%64, %65, %66, %67}, %68, p, 1, 1, %70;\n}\n"
    : "+f"(d[0]), "+f"(d[1]), "+f"(d[2]), "+f"(d[3]), "+f"(d[4]), "+f"(d[5]), "+f"(d[6]), "+f"(d[7]),
      "+f"(d[8]), "+f"(d[9]), "+f"(d[10]), "+f"(d[11]), "+f"(d[12]), "+f"(d[13]), "+f"(d[14]), "+f"(d[15]),
      "+f"(d[16]), "+f"(d[17]), "+f"(d[18]), "+f"(d[19]), "+f"(d[20]), "+f"(d[21]), "+f"(d[22]), "+f"(d[23]),
      "+f"(d[24]), "+f"(d[25]), "+f"(d[26]), "+f"(d[27]), "+f"(d[28]), "+f"(d[29]), "+f"(d[30]), "+f"(d[31]),
      "+f"(d[32]), "+f"(d[33]), "+f"(d[34]), "+f"(d[35]), "+f"(d[36]), "+f"(d[37]), "+f"(d[38]), "+f"(d[39]),
      "+f"(d[40]), "+f"(d[41]), "+f"(d[42]), "+f"(d[43]), "+f"(d[44]), "+f"(d[45]), "+f"(d[46]), "+f"(d[47]),
      "+f"(d[48]), "+f"(d[49]), "+f"(d[50]), "+f"(d[51]), "+f"(d[52]), "+f"(d[53]), "+f"(d[54]), "+f"(d[55]),
      "+f"(d[56]), "+f"(d[57]), "+f"(d[58]), "+f"(d[59]), "+f"(d[60]), "+f"(d[61]), "+f"(d[62]), "+f"(d[63])
    : "r"(a0), "r"(a1), "r"(a2), "r"(a3), "l"(descB), "r"(scaleD), "n"(TB));
}

template<int TB> __device__ __forceinline__ void wgmma_rs_n64(float (&d)[64], uint32_t a0, uint32_t a1, uint32_t a2, uint32_t a3, uint64_t descB, int scaleD) {
  asm volatile("{\n.reg .pred p;\nsetp.ne.b32 p, %37, 0;\n"
    "wgmma.mma_async.sync.aligned.m64n64k16.f32.bf16.bf16 "
    "{%0, %1, %2, %3, %4, %5, %6, %7, %8, %9, %10, %11, %12, %13, %14, %15, "
    "%16, %17, %18, %19, %20, %21, %22, %23, %24, %25, %26, %27, %28, %29, %30, %31}, "
    "{%32, %33, %34, %35}, %36, p, 1, 1, %38;\n}\n"
    : "+f"(d[0]), "+f"(d[1]), "+f"(d[2]), "+f"(d[3]), "+f"(d[4]), "+f"(d[5]), "+f"(d[6]), "+f"(d[7]),
      "+f"(d[8]), "+f"(d[9]), "+f"(d[10]), "+f"(d[11]), "+f"(d[12]), "+f"(d[13]), "+f"(d[14]), "+f"(d[15]),
      "+f"(d[16]), "+f"(d[17]), "+f"(d[18]), "+f"(d[19]), "+f"(d[20]), "+f"(d[21]), "+f"(d[22]), "+f"(d[23]),
      "+f"(d[24]), "+f"(d[25]), "+f"(d[26]), "+f"(d[27]), "+f"(d[28]), "+f"(d[29]), "+f"(d[30]), "+f"(d[31])
    : "r"(a0), "r"(a1), "r"(a2), "r"(a3), "l"(descB), "r"(scaleD), "n"(TB));
}

struct Cur {
  uint32_t o, phase;
  __device__ __forceinline__ void adv() { o += 8; if (o == 8 * NSLOT) { o = 0; phase ^= 1; } }
};

struct Params {
  CUtensorMap ckv, xn, x, wq, wuk, wuv, wo, out;
  const __nv_bfloat16 *px, *w_r, *w_gate, *w_up, *w_down;
  float neg;
};

__device__ __forceinline__ void moe_cta(const Params& P, int q, unsigned ep, uint8_t* smem) {
  float* xs = (float*)smem;
  float* red = xs + DM;
  float* hs = red + 2 * 8 * 344;
  float* sv = hs + 344; int* si = (int*)(sv + 16);
  const int tid = threadIdx.x, lane = tid & 31, warp = tid >> 5;
  if (tid < 16) flag_wait(F_LN + tid, ep * 8);
  __syncthreads();
  float bv = -INFINITY; int bi = 0x7fffffff;
  for (int i = tid; i < SEQ; i += 384) { float v = __ldcg(&g_r[i]); if (v > bv || bi == 0x7fffffff) { bv = v; bi = i; } }
#pragma unroll
  for (int o = 16; o; o >>= 1) {
    float ov = __shfl_xor_sync(~0u, bv, o); int oi = __shfl_xor_sync(~0u, bi, o);
    if (ov > bv || (ov == bv && oi < bi)) { bv = ov; bi = oi; }
  }
  if (lane == 0) { sv[warp] = bv; si[warp] = bi; }
  __syncthreads();
  bv = sv[0]; bi = si[0];
  for (int w = 1; w < 12; w++) { float ov = sv[w]; int oi = si[w]; if (ov > bv || (ov == bv && oi < bi)) { bv = ov; bi = oi; } }
  for (int i = tid; i < DM; i += 384) xs[i] = __bfloat162float(__ldcg(&g_xn[bi * DM + i]));
  __syncthreads();
  const int f0 = q * 344;
  if (tid < 344) {
    const int cg = tid % 43, ksl = tid / 43;
    float ag[8], au[8];
#pragma unroll
    for (int i = 0; i < 8; i++) ag[i] = au[i] = 0.f;
    const __nv_bfloat16* pg = P.w_gate + (size_t)(ksl * 64) * FF + f0 + cg * 8;
    const __nv_bfloat16* pu = P.w_up + (size_t)(ksl * 64) * FF + f0 + cg * 8;
#pragma unroll 8
    for (int k = 0; k < 64; k++) {
      uint4 a = __ldg((const uint4*)(pg + (size_t)k * FF)), b = __ldg((const uint4*)(pu + (size_t)k * FF));
      float xv = xs[ksl * 64 + k];
      ag[0] += xv * bf_lo(a.x); ag[1] += xv * bf_hi(a.x); ag[2] += xv * bf_lo(a.y); ag[3] += xv * bf_hi(a.y);
      ag[4] += xv * bf_lo(a.z); ag[5] += xv * bf_hi(a.z); ag[6] += xv * bf_lo(a.w); ag[7] += xv * bf_hi(a.w);
      au[0] += xv * bf_lo(b.x); au[1] += xv * bf_hi(b.x); au[2] += xv * bf_lo(b.y); au[3] += xv * bf_hi(b.y);
      au[4] += xv * bf_lo(b.z); au[5] += xv * bf_hi(b.z); au[6] += xv * bf_lo(b.w); au[7] += xv * bf_hi(b.w);
    }
#pragma unroll
    for (int i = 0; i < 8; i++) { red[ksl * 344 + cg * 8 + i] = ag[i]; red[(8 + ksl) * 344 + cg * 8 + i] = au[i]; }
  }
  __syncthreads();
  if (tid < 344) {
    float g = 0.f, u = 0.f;
#pragma unroll
    for (int i = 0; i < 8; i++) { g += red[i * 344 + tid]; u += red[(8 + i) * 344 + tid]; }
    g = rbf(g); u = rbf(u);
    g = rbf(g / (1.f + expf(-g)));
    hs[tid] = rbf(g * u);
  }
  __syncthreads();
  {
    const int cg = tid & 63, fs = tid >> 6;
    float ay[8];
#pragma unroll
    for (int i = 0; i < 8; i++) ay[i] = 0.f;
    const __nv_bfloat16* pd = P.w_down + (size_t)f0 * DM + cg * 8;
#pragma unroll 8
    for (int f = fs; f < 344; f += 6) {
      uint4 a = __ldg((const uint4*)(pd + (size_t)f * DM));
      float hv = hs[f];
      ay[0] += hv * bf_lo(a.x); ay[1] += hv * bf_hi(a.x); ay[2] += hv * bf_lo(a.y); ay[3] += hv * bf_hi(a.y);
      ay[4] += hv * bf_lo(a.z); ay[5] += hv * bf_hi(a.z); ay[6] += hv * bf_lo(a.w); ay[7] += hv * bf_hi(a.w);
    }
#pragma unroll
    for (int i = 0; i < 8; i++) red[fs * DM + cg * 8 + i] = ay[i];
  }
  __syncthreads();
  for (int i = tid; i < DM; i += 384) {
    float y = 0.f;
#pragma unroll
    for (int s = 0; s < 6; s++) y += red[s * DM + i];
    g_ypart[q * DM + i] = y;
  }
  if (q == 0 && tid == 0) { g_sel = bi; g_gate = rbf(1.f / (1.f + expf(-bv))); }
  __syncthreads();
  if (tid == 0) { __threadfence(); flag_add(F_MOE); }
}

__device__ __forceinline__ void ln_rows(const Params& P, int row0, int lane) {
  const uint4* px = (const uint4*)(P.px + (size_t)row0 * DM) + lane;
  uint4 na = __ldg(px), nb = __ldg(px + 32);
#pragma unroll 1
  for (int i = 0; i < 16; i++) {
    uint32_t x[8] = {na.x, na.y, na.z, na.w, nb.x, nb.y, nb.z, nb.w};
    if (i < 15) { na = __ldg(px + 64 * (i + 1)); nb = __ldg(px + 64 * (i + 1) + 32); }
    float s = 0.f;
#pragma unroll
    for (int k = 0; k < 8; k++) s += bf_lo(x[k]) + bf_hi(x[k]);
#pragma unroll
    for (int o = 16; o; o >>= 1) s += __shfl_xor_sync(~0u, s, o);
    const float mean = s * (1.f / DM);
    float ss = 0.f;
#pragma unroll
    for (int k = 0; k < 8; k++) { const float d0 = bf_lo(x[k]) - mean, d1 = bf_hi(x[k]) - mean; ss = fmaf(d0, d0, fmaf(d1, d1, ss)); }
#pragma unroll
    for (int o = 16; o; o >>= 1) ss += __shfl_xor_sync(~0u, ss, o);
    const float mb = rbf(mean);
    const float sd = rbf(sqrtf(rbf(rbf(ss * (1.f / DM)) + 1e-5f)));
    const float rs = 1.f / sd;
#pragma unroll
    for (int k = 0; k < 8; k++) {
      const uint32_t d = pack_bf16(bf_lo(x[k]) - mb, bf_hi(x[k]) - mb);
      float q0 = bf_lo(d) * rs, q1 = bf_hi(d) * rs;
      q0 = fmaf(fmaf(-q0, sd, bf_lo(d)), rs, q0); q1 = fmaf(fmaf(-q1, sd, bf_hi(d)), rs, q1);
      x[k] = pack_bf16(q0, q1);
    }
    uint4* dst = (uint4*)(g_xn + (size_t)(row0 + i) * DM) + lane;
    dst[0] = make_uint4(x[0], x[1], x[2], x[3]);
    dst[32] = make_uint4(x[4], x[5], x[6], x[7]);
    float r = 0.f;
#pragma unroll
    for (int h = 0; h < 2; h++) {
      const uint4 w = __ldg((const uint4*)P.w_r + 32 * h + lane);
      r = fmaf(bf_lo(x[4 * h]), bf_lo(w.x), fmaf(bf_hi(x[4 * h]), bf_hi(w.x), r));
      r = fmaf(bf_lo(x[4 * h + 1]), bf_lo(w.y), fmaf(bf_hi(x[4 * h + 1]), bf_hi(w.y), r));
      r = fmaf(bf_lo(x[4 * h + 2]), bf_lo(w.z), fmaf(bf_hi(x[4 * h + 2]), bf_hi(w.z), r));
      r = fmaf(bf_lo(x[4 * h + 3]), bf_lo(w.w), fmaf(bf_hi(x[4 * h + 3]), bf_hi(w.w), r));
    }
#pragma unroll
    for (int o = 16; o; o >>= 1) r += __shfl_xor_sync(~0u, r, o);
    if (lane == 0) g_r[row0 + i] = rbf(r);
  }
}

struct Ctx {
  uint32_t sb;
  uint32_t dlo;
  uint32_t full0;
  uint32_t rel;
  bool rel_pred;
  uint32_t stg;
  uint32_t stg_full, stg_empty;
  uint32_t stg_phase;
  uint32_t frag_off;
  uint32_t frag_x;
  int w;
  float neg;
  __device__ __forceinline__ void wait(const Cur& c) const { mbar_wait(full0 + c.o, c.phase); }
  __device__ __forceinline__ void release(const Cur& c) const { mbar_arrive_cluster_if(rel + c.o, rel_pred); }
  __device__ __forceinline__ void skip(const Cur& c) const { if (rel_pred) { wait(c); release(c); } __syncwarp(); }
  __device__ __forceinline__ uint32_t addr(const Cur& c) const { return sb + c.o * (TILE / 8); }
  __device__ __forceinline__ uint32_t dsc(const Cur& c) const { return dlo + c.o * (TILE / 128); }
  __device__ __forceinline__ void turn_begin() const { bar_sync(1 + w, 256); }
  __device__ __forceinline__ void turn_end() const { bar_arrive(2 - w, 256); }
  __device__ __forceinline__ uint32_t frag(int jj, int hstride) const { return (jj >> 2) * hstride + frag_off + (((jj & 3) * 32) ^ frag_x); }
  template <bool SCALE> __device__ __forceinline__ void stage_out(const float (&d)[64], float s0, float s1) {
    mbar_wait(stg_empty, stg_phase ^ 1);
    stg_phase ^= 1;
#pragma unroll
    for (int jj = 0; jj < 8; jj++) {
      if (SCALE)
        stsm4(stg + frag(jj, 8192), pack_bf16(d[8 * jj] * s0, d[8 * jj + 1] * s0), pack_bf16(d[8 * jj + 2] * s1, d[8 * jj + 3] * s1),
              pack_bf16(d[8 * jj + 4] * s0, d[8 * jj + 5] * s0), pack_bf16(d[8 * jj + 6] * s1, d[8 * jj + 7] * s1));
      else
        stsm4(stg + frag(jj, 8192), pack_bf16(d[8 * jj], d[8 * jj + 1]), pack_bf16(d[8 * jj + 2], d[8 * jj + 3]),
              pack_bf16(d[8 * jj + 4], d[8 * jj + 5]), pack_bf16(d[8 * jj + 6], d[8 * jj + 7]));
    }
  }
  __device__ __forceinline__ void publish() const { fence_async_smem(); mbar_arrive(stg_full); }
};

constexpr float SM_SCALE = 0.08838834764831845f * 1.4426950408889634f;
constexpr float SUM_LIMIT = 1152921504606846976.f;

struct Attn {
  float o[64], s[64];
  uint32_t p[32], q[32];
  float n0, n1;
  float l0, l1;
};

__device__ __forceinline__ void issue_qk(Attn& A, uint32_t d) {
#pragma unroll
  for (int kk = 0; kk < 8; kk++)
    wgmma_rs_n128<0>(A.s, A.q[4 * kk], A.q[4 * kk + 1], A.q[4 * kk + 2], A.q[4 * kk + 3], desc(d + (((kk >> 2) * HALF + (kk & 3) * 32) >> 4)), kk > 0);
  wg_commit();
}
__device__ __forceinline__ void issue_pv(Attn& A, uint32_t d, int acc) {
#pragma unroll
  for (int kk = 0; kk < 8; kk++)
    wgmma_rs_n128<1>(A.o, A.p[4 * kk], A.p[4 * kk + 1], A.p[4 * kk + 2], A.p[4 * kk + 3], desc(d + ((kk * 2048) >> 4)), kk > 0 ? 1 : acc);
  wg_commit();
}
__device__ __forceinline__ void pack_p(Attn& A) {
#pragma unroll
  for (int i = 0; i < 32; i++) A.p[i] = pack_bf16(A.s[2 * i], A.s[2 * i + 1]);
}
__device__ __forceinline__ void block_max(const Attn& A, float& n0, float& n1) {
  float x0 = fmaxf(A.s[0], A.s[1]), x1 = fmaxf(A.s[2], A.s[3]);
  float y0 = fmaxf(A.s[4], A.s[5]), y1 = fmaxf(A.s[6], A.s[7]);
#pragma unroll
  for (int j = 2; j < 16; j += 2) {
    x0 = fmaxf(x0, fmaxf(A.s[4 * j], A.s[4 * j + 1])); x1 = fmaxf(x1, fmaxf(A.s[4 * j + 2], A.s[4 * j + 3]));
    y0 = fmaxf(y0, fmaxf(A.s[4 * j + 4], A.s[4 * j + 5])); y1 = fmaxf(y1, fmaxf(A.s[4 * j + 6], A.s[4 * j + 7]));
  }
  x0 = fmaxf(x0, y0); x1 = fmaxf(x1, y1);
  x0 = fmaxf(x0, __shfl_xor_sync(~0u, x0, 1)); x1 = fmaxf(x1, __shfl_xor_sync(~0u, x1, 1));
  x0 = fmaxf(x0, __shfl_xor_sync(~0u, x0, 2)); x1 = fmaxf(x1, __shfl_xor_sync(~0u, x1, 2));
  n0 = -x0 * SM_SCALE; n1 = -x1 * SM_SCALE;
}
template <int J0, int J1> __device__ __forceinline__ void exp_cols(Attn& A, float (&a)[4]) {
#pragma unroll
  for (int j = J0; j < J1; j++) {
    A.s[4 * j] = ex2(fmaf(A.s[4 * j], SM_SCALE, A.n0)); A.s[4 * j + 1] = ex2(fmaf(A.s[4 * j + 1], SM_SCALE, A.n0));
    A.s[4 * j + 2] = ex2(fmaf(A.s[4 * j + 2], SM_SCALE, A.n1)); A.s[4 * j + 3] = ex2(fmaf(A.s[4 * j + 3], SM_SCALE, A.n1));
    if (j == 0) { a[0] = A.s[0]; a[1] = A.s[1]; a[2] = A.s[2]; a[3] = A.s[3]; }
    else { a[0] += A.s[4 * j]; a[1] += A.s[4 * j + 1]; a[2] += A.s[4 * j + 2]; a[3] += A.s[4 * j + 3]; }
  }
}
__device__ __forceinline__ void pin(float v, float neg, uint32_t addr) {
  asm volatile("{\n.reg .pred p;\nsetp.lt.f32 p, %0, %2;\n@p mbarrier.arrive.shared::cta.b64 _, [%1];\n}" :: "f"(v), "r"(addr), "f"(neg) : "memory");
}
__device__ __forceinline__ void causal_mask(Attn& A, int rel) {
#pragma unroll
  for (int j = 0; j < 16; j++) {
    if (8 * j > rel) A.s[4 * j] = -INFINITY;
    if (8 * j + 1 > rel) A.s[4 * j + 1] = -INFINITY;
    if (8 * j > rel + 8) A.s[4 * j + 2] = -INFINITY;
    if (8 * j + 1 > rel + 8) A.s[4 * j + 3] = -INFINITY;
  }
}
__device__ __forceinline__ void finish_item(Ctx& C, Attn& A, float l0, float l1) {
  l0 += __shfl_xor_sync(~0u, l0, 1); l1 += __shfl_xor_sync(~0u, l1, 1);
  l0 += __shfl_xor_sync(~0u, l0, 2); l1 += __shfl_xor_sync(~0u, l1, 2);
  C.stage_out<true>(A.o, __fdividef(1.f, l0), __fdividef(1.f, l1));
}
__device__ __forceinline__ void redo_block(Attn& A, const uint8_t* ktile, bool diag, int rel) {
  const int lane = threadIdx.x & 31;
  const uint8_t* kp = ktile + (lane >> 2) * 128 + (lane & 3) * 4;
  const int sw = (lane >> 2) * 16;
#pragma unroll
  for (int j = 0; j < 16; j++) {
    float c0 = 0.f, c1 = 0.f, c2 = 0.f, c3 = 0.f;
#pragma unroll
    for (int kk = 0; kk < 8; kk++) {
      const uint32_t b0 = __ldcg((const uint32_t*)(kp + j * 1024 + (kk >> 2) * HALF + (((kk & 3) * 32) ^ sw)));
      const uint32_t b1 = __ldcg((const uint32_t*)(kp + j * 1024 + (kk >> 2) * HALF + (((kk & 3) * 32 + 16) ^ sw)));
      asm volatile("mma.sync.aligned.m16n8k16.row.col.f32.bf16.bf16.f32 {%0, %1, %2, %3}, {%4, %5, %6, %7}, {%8, %9}, {%0, %1, %2, %3};"
                   : "+f"(c0), "+f"(c1), "+f"(c2), "+f"(c3)
                   : "r"(A.q[4 * kk]), "r"(A.q[4 * kk + 1]), "r"(A.q[4 * kk + 2]), "r"(A.q[4 * kk + 3]), "r"(b0), "r"(b1) : "memory");
    }
    A.s[4 * j] = c0; A.s[4 * j + 1] = c1; A.s[4 * j + 2] = c2; A.s[4 * j + 3] = c3;
  }
  if (diag) causal_mask(A, rel);
  float n0, n1, a[4];
  block_max(A, n0, n1);
  n0 = fminf(n0, A.n0); n1 = fminf(n1, A.n1);
  const float c0 = ex2(n0 - A.n0), c1 = ex2(n1 - A.n1);
  A.n0 = n0; A.n1 = n1;
  exp_cols<0, 16>(A, a);
  A.l0 = fmaf(A.l0, c0, a[0] + a[1]); A.l1 = fmaf(A.l1, c1, a[2] + a[3]);
#pragma unroll
  for (int j = 0; j < 16; j++) { A.o[4 * j] *= c0; A.o[4 * j + 1] *= c0; A.o[4 * j + 2] *= c1; A.o[4 * j + 3] *= c1; }
  pack_p(A);
}
template <bool HAS_PREV> __device__ __forceinline__ void item_begin(Ctx& C, Attn& A, Cur& cur, bool skip, int pv_acc, bool pub, bool diag, int rel) {
  Cur cq, ck, cv, cs;
  if (HAS_PREV && skip) { C.skip(cur); cur.adv(); cv = cur; cur.adv(); }
  cq = cur; cur.adv();
  ck = cur; cur.adv();
  if (HAS_PREV) { cs = cur; cur.adv(); if (!skip) cv = cs; }
  C.wait(cq);
  {
    const uint32_t qa = C.addr(cq) + C.w * 8192;
#pragma unroll
    for (int jj = 0; jj < 8; jj++) ldsm4(qa + C.frag(jj, HALF), A.q[4 * jj], A.q[4 * jj + 1], A.q[4 * jj + 2], A.q[4 * jj + 3]);
  }
  C.wait(ck);
  C.turn_begin();
  wg_fence();
  issue_qk(A, C.dsc(ck));
  if (HAS_PREV) { C.wait(cv); wg_fence(); issue_pv(A, C.dsc(cv), pv_acc); }
  C.turn_end();
  if (pub) C.publish();
  if (HAS_PREV) wg_wait<1>(); else wg_wait<0>();
  reg_fence(A.s);
  C.release(cq); C.release(ck);
  if (diag) causal_mask(A, rel);
  block_max(A, A.n0, A.n1);
  if (HAS_PREV) {
    wg_wait<0>();
    reg_fence(A.o);
    C.release(cv);
    finish_item(C, A, A.l0, A.l1);
  }
  float a[4];
  exp_cols<0, 16>(A, a);
  A.l0 = a[0] + a[1]; A.l1 = a[2] + a[3];
  pack_p(A);
  if (HAS_PREV && skip) C.skip(cs);
}
__device__ __forceinline__ void item_step(Ctx& C, Attn& A, Cur& cur, int pv_acc, bool pub, bool diag, int rel, const uint8_t* ktile) {
  const Cur ck = cur; cur.adv();
  const Cur cv = cur; cur.adv();
  C.wait(ck);
  C.turn_begin();
  wg_fence();
  issue_qk(A, C.dsc(ck));
  C.wait(cv);
  wg_fence();
  issue_pv(A, C.dsc(cv), pv_acc);
  C.turn_end();
  if (pub) C.publish();
  wg_wait<1>();
  reg_fence(A.s);
  C.release(ck);
  if (diag) causal_mask(A, rel);
  float a[4];
  exp_cols<0, 8>(A, a);
  pin((a[0] + a[1]) + (a[2] + a[3]), C.neg, C.stg_full);
  wg_wait<0>();
  reg_fence(A.o);
  C.release(cv);
  exp_cols<8, 16>(A, a);
  pack_p(A);
  const float b0 = a[0] + a[1], b1 = a[2] + a[3];
  if (__builtin_expect(__any_sync(~0u, !(b0 + b1 <= SUM_LIMIT)), 0)) redo_block(A, ktile, diag, rel);
  else { A.l0 += b0; A.l1 += b1; }
}

template <bool LOAD_A> __device__ __forceinline__ void proj_unit(Ctx& C, Cur& cur, uint32_t (&a)[128], float (&acc)[64], bool pub) {
#pragma unroll
  for (int i = 0; i < 4; i++) {
    Cur ca = cur;
    if (LOAD_A) {
      cur.adv();
      C.wait(ca);
      const uint32_t aa = C.addr(ca) + C.w * 8192;
#pragma unroll
      for (int jj = 0; jj < 8; jj++) ldsm4(aa + C.frag(jj, HALF), a[32 * i + 4 * jj], a[32 * i + 4 * jj + 1], a[32 * i + 4 * jj + 2], a[32 * i + 4 * jj + 3]);
    }
    const Cur cb = cur; cur.adv();
    C.wait(cb);
    C.turn_begin();
    wg_fence();
    const uint32_t d = C.dsc(cb);
#pragma unroll
    for (int kk = 0; kk < 8; kk++)
      wgmma_rs_n128<1>(acc, a[32 * i + 4 * kk], a[32 * i + 4 * kk + 1], a[32 * i + 4 * kk + 2], a[32 * i + 4 * kk + 3], desc(d + ((kk * 2048) >> 4)), (i | kk) > 0);
    wg_commit();
    C.turn_end();
    if (i == 0 && pub) C.publish();
    wg_wait<0>();
    reg_fence(acc);
    if (LOAD_A) C.release(ca);
    C.release(cb);
  }
  C.stage_out<false>(acc, 1.f, 1.f);
}

__global__ void __cluster_dims__(2, 1, 1) __launch_bounds__(384, 1) fused_kernel(const __grid_constant__ Params P) {
  extern __shared__ uint8_t smem_raw[];
  uint8_t* smem = smem_raw + ((1024 - (smem_u32(smem_raw) & 1023)) & 1023);
  const int tid = threadIdx.x;
  const int c = blockIdx.x >> 1, r = blockIdx.x & 1;
  const unsigned ep = g_epoch[blockIdx.x] + 1;
  if (c >= 64) {
    moe_cta(P, blockIdx.x - 128, ep, smem);
    if (tid == 0) g_epoch[blockIdx.x] = ep;
    return;
  }
  const uint32_t sb = smem_u32(smem);
  const uint32_t full0 = sb + SMEM_BAR, empty0 = full0 + 8 * NSLOT, stgf0 = empty0 + 8 * NSLOT, stge0 = stgf0 + 16;
  if (tid == 0) {
    for (int i = 0; i < NSLOT; i++) { mbar_init(full0 + 8 * i, 1); mbar_init(empty0 + 8 * i, 4); }
    for (int i = 0; i < 2; i++) { mbar_init(stgf0 + 8 * i, 128); mbar_init(stge0 + 8 * i, 1); }
    asm volatile("fence.mbarrier_init.release.cluster;" ::: "memory");
  }
  asm volatile("barrier.cluster.arrive.aligned;\nbarrier.cluster.wait.aligned;" ::: "memory");

  const int rp = c & 7, g = c >> 3;
  const int rb = 2 * rp + r;
  const int ma = rp & 3, hb = rp >> 2;
  const int j3 = c & 15, ks = c >> 5, ncol = 2 * ((c >> 4) & 1) + r;
  const int wg = __shfl_sync(~0u, tid >> 7, 0);

  if (wg == 0) {
    asm volatile("setmaxnreg.dec.sync.aligned.u32 40;");
    const int warp = tid >> 5;
    if (warp == 0) {
      if (tid == 0) {
        Cur cur{0, 0};
        uint32_t dst, bar;
        auto acquire = [&]() {
          mbar_wait(empty0 + cur.o, cur.phase ^ 1);
          dst = sb + cur.o * (TILE / 8); bar = full0 + cur.o;
          mbar_expect(bar, TILE);
          cur.adv();
        };
        for (int u = 0; u < 12; u++) {
          const CUtensorMap* wm = u >= 8 ? &P.wq : ((u & 1) ? &P.wuv : &P.wuk);
          const CUtensorMap* am = u >= 8 ? &P.xn : &P.ckv;
          const int head = 4 * g + (u >= 8 ? u - 8 : u >> 1);
          if (u == 8) { flag_wait(F_LN + rb, ep * 8); fence_async_all(); }
          for (int i = 0; i < 4; i++) {
            if ((u & 7) == 0) {
              acquire();
              tma_load(dst, am, 128 * i, rb * 128, bar);
              tma_load(dst + HALF, am, 128 * i + 64, rb * 128, bar);
            }
            acquire();
            tma_load_mc(dst + r * HALF, wm, head * 128 + 64 * r, 128 * i, bar);
          }
        }
        const uint8_t* prev_v = nullptr;
        for (int it = 0; it < 4; it++) {
          const int head = 4 * g + (it & 2) + hb;
          const int m = (it & 1) ? ma : 7 - ma;
          const int j = 2 * m + (r ^ (it & 1));
          if (!(it & 1)) { flag_wait(F_HEAD + head, ep * 32); fence_async_all(); }
          acquire();
          bulk_load(dst, g_qkv + (size_t)(head * 16 + j) * TILE, TILE, bar);
          for (int b = 0; b <= 2 * m + 1; b++) {
            acquire();
            bulk_load_mc(dst + r * HALF, g_qkv + (size_t)((NH + head) * 16 + b) * TILE + r * HALF, HALF, bar);
            if (prev_v) { acquire(); bulk_load_mc(dst + r * HALF, prev_v, HALF, bar); }
            prev_v = g_qkv + (size_t)((2 * NH + head) * 16 + b) * TILE + r * HALF;
          }
        }
        acquire(); bulk_load_mc(dst + r * HALF, prev_v, HALF, bar);
        for (int t = 0; t < 16; t++) {
          const int head = 16 * ks + 4 * ((t & 7) >> 1) + 2 * (t >> 3) + (t & 1);
          acquire();
          tma_load(dst + ks * HALF, &P.wo, ncol * 128, head * 128, bar);
          tma_load(dst + (ks ^ 1) * HALF, &P.wo, ncol * 128 + 64, head * 128, bar);
          if ((t & 7) == 0) { flag_wait(F_CTX + j3 * 4 + ks * 2 + (t >> 3), ep * 16); fence_async_all(); }
          acquire();
          bulk_load_mc(dst + r * HALF, g_ctx + (size_t)(head * 16 + j3) * TILE + r * HALF, HALF, bar);
        }
        flag_wait(F_LN + j3, ep * 8);
        flag_wait(F_MOE, ep * 4);
        fence_async_all();
        acquire();
        tma_load(dst, &P.x, ncol * 128 + 64 * ks, j3 * 128, bar);
        tma_load(dst + HALF, &P.xn, ncol * 128 + 64 * ks, j3 * 128, bar);
        for (int i = 0; i < NSLOT; i++) { mbar_wait(empty0 + cur.o, cur.phase ^ 1); cur.adv(); }
        g_epoch[blockIdx.x] = ep;
      }
    } else if (warp < 3) {
      if ((tid & 31) == 0) {
        const int w = warp - 1;
        const uint32_t stg = sb + SMEM_STG + w * HALF;
        for (int job = 0; job < 17; job++) {
          mbar_wait(stgf0 + 8 * w, job & 1);
          int flag = -1;
          if (job < 16) {
            uint8_t* d;
            if (job < 12) {
              const int head = 4 * g + (job >= 8 ? job - 8 : job >> 1);
              const int kind = job >= 8 ? 0 : 1 + (job & 1);
              d = g_qkv + (size_t)((kind * NH + head) * 16 + rb) * TILE;
              if (job >= 8) flag = F_HEAD + head;
            } else {
              const int it = job - 12;
              const int head = 4 * g + (it & 2) + hb;
              const int m = (it & 1) ? ma : 7 - ma;
              const int j = 2 * m + (r ^ (it & 1));
              d = g_ctx + (size_t)(head * 16 + j) * TILE;
              flag = F_CTX + j * 4 + (g >> 2) * 2 + (it >> 1);
            }
            bulk_store(d + w * 8192, stg, 8192);
            bulk_store(d + HALF + w * 8192, stg + 8192, 8192);
          } else {
            tma_store(&P.out, ncol * 128 + 64 * ks, j3 * 128 + 64 * w, stg);
          }
          asm volatile("cp.async.bulk.commit_group;" ::: "memory");
          asm volatile("cp.async.bulk.wait_group.read 0;" ::: "memory");
          mbar_arrive(stge0 + 8 * w);
          if (job >= 8) asm volatile("cp.async.bulk.wait_group 0;" ::: "memory");
          if (flag >= 0) { fence_async_all(); flag_add(flag); }
        }
      }
    } else {
      ln_rows(P, rb * 128 + 16 * g, tid & 31);
      __syncwarp();
      if (tid == 96) { __threadfence(); fence_async_all(); flag_add(F_LN + rb); }
    }
  } else {
    asm volatile("setmaxnreg.inc.sync.aligned.u32 232;");
    const int t = tid & 127, lane = tid & 31, wi = t >> 5;
    Ctx C;
    C.neg = P.neg; C.sb = sb; C.dlo = desc_lo(sb); C.full0 = full0; C.w = wg - 1;
    asm("mapa.shared::cluster.u32 %0, %1, %2;" : "=r"(C.rel) : "r"(empty0), "r"(lane & 1));
    C.rel_pred = t < 2;
    C.stg = sb + SMEM_STG + C.w * HALF;
    C.stg_full = stgf0 + 8 * C.w; C.stg_empty = stge0 + 8 * C.w; C.stg_phase = 0;
    C.frag_off = (16 * wi + (lane & 15)) * 128;
    C.frag_x = ((lane >> 4) ^ (lane & 7)) * 16;
    TL(C.w * 16 + 0);
    if (C.w == 1) bar_arrive(1, 256);
    Cur cur{0, 0};
    TL(C.w * 16 + 1);
    {
      uint32_t a[128];
      float acc[64];
#pragma unroll 1
      for (int half = 0; half < 2; half++) {
        proj_unit<true>(C, cur, a, acc, half);
        if (half == 0) TL(C.w * 16 + 2);
#pragma unroll 1
        for (int u = half ? 5 : 1; u < 8; u++) proj_unit<false>(C, cur, a, acc, true);
      }
    }
    TL(C.w * 16 + 3);
    {
      Attn A;
      const int rel = 64 * C.w + 16 * wi + (lane >> 2) - 2 * (lane & 3);
      A.l0 = A.l1 = 0.f;
      int pv_acc = 0;
      bool skip = false, pub = true;
#pragma unroll 1
      for (int it = 0; it < 4; it++) {
        const int m = (it & 1) ? ma : 7 - ma;
        const int role = r ^ (it & 1);
        const int j = 2 * m + role;
        if (it == 0) item_begin<false>(C, A, cur, false, 0, true, j == 0, rel);
        else item_begin<true>(C, A, cur, skip, pv_acc, pub, j == 0, rel);
        pv_acc = 0; pub = it > 0; skip = role == 0;
        const uint8_t* kt = g_qkv + (size_t)((NH + 4 * g + (it & 2) + hb) * 16) * TILE;
#pragma unroll 1
        for (int b = 1; b <= j; b++) { item_step(C, A, cur, pv_acc, pub, b == j, rel, kt + (size_t)b * TILE); pv_acc = 1; pub = false; }
        TL(C.w * 16 + 4 + it);
      }
      if (skip) { C.skip(cur); cur.adv(); }
      const Cur cv = cur; cur.adv();
      C.wait(cv);
      C.turn_begin();
      wg_fence();
      issue_pv(A, C.dsc(cv), pv_acc);
      C.turn_end();
      if (pub) C.publish();
      wg_wait<0>();
      reg_fence(A.o);
      C.release(cv);
      finish_item(C, A, A.l0, A.l1);
      C.publish();
      if (skip) { C.skip(cur); cur.adv(); }
      if (C.w == 0) C.turn_begin();
    }
    TL(C.w * 16 + 8);
    {
      float acc[64];
      Cur pb = cur, pa = cur;
#pragma unroll 1
      for (int h = 0; h < 16; h++) {
        const Cur cb = cur; cur.adv();
        const Cur ca = cur; cur.adv();
        C.wait(cb); C.wait(ca);
        wg_fence();
        const uint32_t da = C.dsc(ca) + C.w * 512, db = C.dsc(cb);
#pragma unroll
        for (int kk = 0; kk < 8; kk++)
          wgmma_ss_n128<1>(acc, desc(da + (((kk >> 2) * HALF + (kk & 3) * 32) >> 4)), desc(db + ((kk * 2048) >> 4)), kk > 0 ? 1 : h);
        wg_commit();
        wg_wait<1>();
        if (h > 0) { C.release(pb); C.release(pa); }
        pb = cb; pa = ca;
      }
      wg_wait<0>();
      reg_fence(acc);
      C.release(pb); C.release(pa);
      TL(C.w * 16 + 9);
      float4* mine = g_part + (size_t)blockIdx.x * 2048 + C.w * 1024 + t;
      const float4* theirs = g_part + (size_t)(blockIdx.x ^ 64) * 2048 + C.w * 1024 + t;
#pragma unroll
      for (int i = 0; i < 8; i++) __stcg(mine + i * 128, make_float4(acc[32 + 4 * i], acc[33 + 4 * i], acc[34 + 4 * i], acc[35 + 4 * i]));
      bar_sync(4 + C.w, 128);
      if (t == 0) {
        __threadfence();
        flag_add(F_PART + blockIdx.x * 2 + C.w);
        flag_wait(F_PART + (blockIdx.x ^ 64) * 2 + C.w, ep);
      }
      const Cur cr = cur;
      C.wait(cr);
      uint32_t xr[16], nr[16];
      const uint32_t xa = C.addr(cr) + C.w * 8192;
#pragma unroll
      for (int jj = 0; jj < 4; jj++) {
        ldsm4(xa + C.frag(jj, 0), xr[4 * jj], xr[4 * jj + 1], xr[4 * jj + 2], xr[4 * jj + 3]);
        ldsm4(xa + HALF + C.frag(jj, 0), nr[4 * jj], nr[4 * jj + 1], nr[4 * jj + 2], nr[4 * jj + 3]);
      }
      const int sel = __ldcg(&g_sel);
      const int row0 = j3 * 128 + 64 * C.w + 16 * wi + (lane >> 2);
      if (sel == row0 || sel == row0 + 8) {
        const float gate = __ldcg(&g_gate);
        const float* yp = g_ypart + ncol * 128 + 64 * ks + 2 * (lane & 3);
#pragma unroll
        for (int j = 0; j < 8; j++) {
          float y0 = 0.f, y1 = 0.f;
#pragma unroll
          for (int q = 0; q < 4; q++) { y0 += __ldcg(yp + q * DM + 8 * j); y1 += __ldcg(yp + q * DM + 8 * j + 1); }
          y0 = rbf(rbf(y0) * gate); y1 = rbf(rbf(y1) * gate);
          if (sel == row0) nr[2 * j] = pack_bf16(bf_lo(nr[2 * j]) + y0, bf_hi(nr[2 * j]) + y1);
          else nr[2 * j + 1] = pack_bf16(bf_lo(nr[2 * j + 1]) + y0, bf_hi(nr[2 * j + 1]) + y1);
        }
      }
      bar_sync(4 + C.w, 128);
      C.release(cr);
      TL(C.w * 16 + 10);
#pragma unroll
      for (int i = 0; i < 8; i++) {
        const float4 v = __ldcg(theirs + i * 128);
        acc[4 * i] += v.x; acc[4 * i + 1] += v.y; acc[4 * i + 2] += v.z; acc[4 * i + 3] += v.w;
      }
      uint32_t o[16];
#pragma unroll
      for (int i = 0; i < 16; i++)
        o[i] = pack_bf16(rbf(bf_lo(xr[i]) + rbf(acc[2 * i])) + bf_lo(nr[i]), rbf(bf_hi(xr[i]) + rbf(acc[2 * i + 1])) + bf_hi(nr[i]));
      mbar_wait(C.stg_empty, C.stg_phase ^ 1);
#pragma unroll
      for (int jj = 0; jj < 4; jj++) stsm4(C.stg + C.frag(jj, 0), o[4 * jj], o[4 * jj + 1], o[4 * jj + 2], o[4 * jj + 3]);
      fence_async_smem();
      mbar_arrive(C.stg_full);
      TL(C.w * 16 + 11);
    }
  }
}

typedef CUresult (*EncodeFn)(CUtensorMap*, CUtensorMapDataType, cuuint32_t, void*, const cuuint64_t*, const cuuint64_t*,
                             const cuuint32_t*, const cuuint32_t*, CUtensorMapInterleave, CUtensorMapSwizzle,
                             CUtensorMapL2promotion, CUtensorMapFloatOOBfill);

void make_map(EncodeFn fn, CUtensorMap* m, const void* ptr, uint64_t cols, uint64_t rows, uint32_t box_rows) {
  cuuint64_t dims[2] = {cols, rows};
  cuuint64_t strides[1] = {cols * 2};
  cuuint32_t box[2] = {64, box_rows};
  cuuint32_t es[2] = {1, 1};
  fn(m, CU_TENSOR_MAP_DATA_TYPE_BFLOAT16, 2, const_cast<void*>(ptr), dims, strides, box, es, CU_TENSOR_MAP_INTERLEAVE_NONE,
     CU_TENSOR_MAP_SWIZZLE_128B, CU_TENSOR_MAP_L2_PROMOTION_L2_128B, CU_TENSOR_MAP_FLOAT_OOB_FILL_NONE);
}

}

extern "C" void kernel_launch(void* const* d_in, const int* in_sizes, int n_in, void* d_out, int out_size) {
  static EncodeFn fn = nullptr;
  static void* xn_ptr = nullptr;
  if (!fn) {
    void* f = nullptr;
    cudaDriverEntryPointQueryResult qr;
    cudaGetDriverEntryPoint("cuTensorMapEncodeTiled", &f, cudaEnableDefault, &qr);
    fn = (EncodeFn)f;
    cudaGetSymbolAddress(&xn_ptr, g_xn);
    cudaFuncSetAttribute(fused_kernel, cudaFuncAttributeMaxDynamicSharedMemorySize, SMEM_TOTAL);
  }
  Params P;
  make_map(fn, &P.x, d_in[0], DM, SEQ, 128);
  make_map(fn, &P.ckv, d_in[1], DM, SEQ, 128);
  make_map(fn, &P.xn, xn_ptr, DM, SEQ, 128);
  make_map(fn, &P.wq, d_in[2], NH * 128, DM, 128);
  make_map(fn, &P.wuk, d_in[3], NH * 128, DM, 128);
  make_map(fn, &P.wuv, d_in[4], NH * 128, DM, 128);
  make_map(fn, &P.wo, d_in[5], DM, NH * 128, 128);
  make_map(fn, &P.out, d_out, DM, SEQ, 64);
  P.neg = -1.f;
  P.px = (const __nv_bfloat16*)d_in[0];
  P.w_r = (const __nv_bfloat16*)d_in[7];
  P.w_gate = (const __nv_bfloat16*)d_in[8];
  P.w_up = (const __nv_bfloat16*)d_in[9];
  P.w_down = (const __nv_bfloat16*)d_in[10];
  fused_kernel<<<NCTA, 384, SMEM_TOTAL>>>(P);
}
```

```cpp
#include <cuda_runtime.h>
#include <cuda_bf16.h>
#include <cuda.h>
#include <stdint.h>

namespace {

constexpr int SEQ = 2048, DM = 512, NH = 32, FF = 1376;
constexpr int NSLOT = 6;
constexpr int TILE = 32768;
constexpr int HALF = 16384;
constexpr int SMEM_STG = NSLOT * TILE;
constexpr int SMEM_BAR = SMEM_STG + 32768;
constexpr int SMEM_TOTAL = SMEM_BAR + 256 + 1024;
constexpr int NCTA = 132;
constexpr int SPIN_LIMIT = 1 << 22;

constexpr int F_LN = 0;
constexpr int F_HEAD = 16;
constexpr int F_CTX = 48;
constexpr int F_PART = 112;
constexpr int F_MOE = 368;
constexpr int F_COUNT = 369;

__device__ __align__(1024) __nv_bfloat16 g_xn[SEQ * DM];
__device__ float g_r[SEQ];
__device__ __align__(1024) uint8_t g_qkv[3ull * NH * 16 * TILE];
__device__ __align__(1024) uint8_t g_ctx[1ull * NH * 16 * TILE];
__device__ __align__(1024) float4 g_part[128 * 256 * 8];
__device__ float g_ypart[4 * DM];
__device__ int g_sel;
__device__ float g_gate;
__device__ unsigned g_flags[F_COUNT * 32];
__device__ unsigned g_epoch[NCTA];
#define TL(i)
#define TLX(i)

__device__ __forceinline__ uint32_t smem_u32(const void* p) { return (uint32_t)__cvta_generic_to_shared(p); }
__device__ __forceinline__ void mbar_init(uint32_t bar, int cnt) { asm volatile("mbarrier.init.shared::cta.b64 [%0], %1;" :: "r"(bar), "r"(cnt)); }
__device__ __forceinline__ void mbar_arrive(uint32_t bar) { asm volatile("mbarrier.arrive.shared::cta.b64 _, [%0];" :: "r"(bar) : "memory"); }
__device__ __forceinline__ void mbar_arrive_cluster_if(uint32_t bar, bool pred) {
  asm volatile("{\n.reg .pred p;\nsetp.ne.b32 p, %1, 0;\n@p mbarrier.arrive.shared::cluster.b64 _, [%0];\n}" :: "r"(bar), "r"((int)pred) : "memory");
}
__device__ __forceinline__ void mbar_expect(uint32_t bar, int bytes) { asm volatile("mbarrier.arrive.expect_tx.shared::cta.b64 _, [%0], %1;" :: "r"(bar), "r"(bytes) : "memory"); }
__device__ __forceinline__ void mbar_wait(uint32_t bar, uint32_t parity) {
  asm volatile("{\n.reg .pred p, q;\n.reg .b32 n;\n"
               "mbarrier.try_wait.parity.shared::cta.b64 p, [%0], %1;\n@p bra DONE;\nmov.b32 n, 0;\n"
               "LOOP:\nmbarrier.try_wait.parity.shared::cta.b64 p, [%0], %1;\nadd.s32 n, n, 1;\nsetp.lt.s32 q, n, %2;\n@p bra DONE;\n@q bra LOOP;\n"
               "DONE:\n}" :: "r"(bar), "r"(parity), "n"(SPIN_LIMIT) : "memory");
}
__device__ __forceinline__ void bulk_load(uint32_t dst, const void* src, int bytes, uint32_t bar) {
  asm volatile("cp.async.bulk.shared::cluster.global.mbarrier::complete_tx::bytes [%0], [%1], %2, [%3];" :: "r"(dst), "l"(src), "r"(bytes), "r"(bar) : "memory");
}
__device__ __forceinline__ void bulk_load_mc(uint32_t dst, const void* src, int bytes, uint32_t bar) {
  asm volatile("cp.async.bulk.shared::cluster.global.mbarrier::complete_tx::bytes.multicast::cluster [%0], [%1], %2, [%3], %4;" :: "r"(dst), "l"(src), "r"(bytes), "r"(bar), "h"((uint16_t)3) : "memory");
}
__device__ __forceinline__ void tma_load(uint32_t dst, const CUtensorMap* map, int c0, int c1, uint32_t bar) {
  asm volatile("cp.async.bulk.tensor.2d.shared::cluster.global.mbarrier::complete_tx::bytes [%0], [%1, {%3, %4}], [%2];" :: "r"(dst), "l"(map), "r"(bar), "r"(c0), "r"(c1) : "memory");
}
__device__ __forceinline__ void tma_load_mc(uint32_t dst, const CUtensorMap* map, int c0, int c1, uint32_t bar) {
  asm volatile("cp.async.bulk.tensor.2d.shared::cluster.global.mbarrier::complete_tx::bytes.multicast::cluster [%0], [%1, {%3, %4}], [%2], %5;" :: "r"(dst), "l"(map), "r"(bar), "r"(c0), "r"(c1), "h"((uint16_t)3) : "memory");
}
__device__ __forceinline__ void bulk_store(void* dst, uint32_t src, int bytes) {
  asm volatile("cp.async.bulk.global.shared::cta.bulk_group [%0], [%1], %2;" :: "l"(dst), "r"(src), "r"(bytes) : "memory");
}
__device__ __forceinline__ void tma_store(const CUtensorMap* map, int c0, int c1, uint32_t src) {
  asm volatile("cp.async.bulk.tensor.2d.global.shared::cta.bulk_group [%0, {%2, %3}], [%1];" :: "l"(map), "r"(src), "r"(c0), "r"(c1) : "memory");
}
__device__ __forceinline__ void fence_async_smem() { asm volatile("fence.proxy.async.shared::cta;" ::: "memory"); }
__device__ __forceinline__ void fence_async_all() { asm volatile("fence.proxy.async;" ::: "memory"); }
__device__ __forceinline__ void flag_add(int f) { asm volatile("red.release.gpu.global.add.u32 [%0], 1;" :: "l"(&g_flags[f * 32]) : "memory"); }
__device__ __forceinline__ void flag_wait(int f, unsigned target) {
  const unsigned* p = &g_flags[f * 32];
  for (int n = 0; n < SPIN_LIMIT; ++n) {
    unsigned v;
    asm volatile("ld.acquire.gpu.global.u32 %0, [%1];" : "=r"(v) : "l"(p) : "memory");
    if ((int)(v - target) >= 0) break;
  }
}
__device__ __forceinline__ void bar_sync(int id, int n) { asm volatile("bar.sync %0, %1;" :: "r"(id), "r"(n) : "memory"); }
__device__ __forceinline__ void bar_arrive(int id, int n) { asm volatile("bar.arrive %0, %1;" :: "r"(id), "r"(n) : "memory"); }
__device__ __forceinline__ void wg_fence() { asm volatile("wgmma.fence.sync.aligned;" ::: "memory"); }
__device__ __forceinline__ void wg_commit() { asm volatile("wgmma.commit_group.sync.aligned;" ::: "memory"); }
template <int N> __device__ __forceinline__ void wg_wait() { asm volatile("wgmma.wait_group.sync.aligned %0;" :: "n"(N) : "memory"); }
template <int N> __device__ __forceinline__ void reg_fence(float (&d)[N]) {
#pragma unroll
  for (int i = 0; i < N; i++) asm volatile("" : "+f"(d[i]) :: "memory");
}
__device__ __forceinline__ void ldsm4(uint32_t addr, uint32_t& r0, uint32_t& r1, uint32_t& r2, uint32_t& r3) {
  asm volatile("ldmatrix.sync.aligned.m8n8.x4.shared.b16 {%0, %1, %2, %3}, [%4];" : "=r"(r0), "=r"(r1), "=r"(r2), "=r"(r3) : "r"(addr) : "memory");
}
__device__ __forceinline__ void stsm4(uint32_t addr, uint32_t r0, uint32_t r1, uint32_t r2, uint32_t r3) {
  asm volatile("stmatrix.sync.aligned.m8n8.x4.shared.b16 [%0], {%1, %2, %3, %4};" :: "r"(addr), "r"(r0), "r"(r1), "r"(r2), "r"(r3) : "memory");
}
__device__ __forceinline__ uint32_t pack_bf16(float lo, float hi) {
  uint32_t r; asm("cvt.rn.bf16x2.f32 %0, %1, %2;" : "=r"(r) : "f"(hi), "f"(lo)); return r;
}
__device__ __forceinline__ float ex2(float x) { float y; asm("ex2.approx.ftz.f32 %0, %1;" : "=f"(y) : "f"(x)); return y; }
__device__ __forceinline__ float bf_lo(uint32_t v) { return __uint_as_float(v << 16); }
__device__ __forceinline__ float bf_hi(uint32_t v) { return __uint_as_float(v & 0xffff0000u); }
__device__ __forceinline__ float rbf(float x) { return __bfloat162float(__float2bfloat16_rn(x)); }

__device__ __forceinline__ uint32_t desc_lo(uint32_t addr) { return ((addr & 0x3FFFF) >> 4) | ((uint32_t)(HALF >> 4) << 16); }
__device__ __forceinline__ uint64_t desc(uint32_t lo) { return (uint64_t)lo | ((uint64_t)(64u | (1u << 30)) << 32); }

template<int TB> __device__ __forceinline__ void wgmma_ss_n128(float (&d)[64], uint64_t descA, uint64_t descB, int scaleD) {
  asm volatile("{\n.reg .pred p;\nsetp.ne.b32 p, %66, 0;\n"
    "wgmma.mma_async.sync.aligned.m64n128k16.f32.bf16.bf16 "
    "{%0, %1, %2, %3, %4, %5, %6, %7, %8, %9, %10, %11, %12, %13, %14, %15, "
    "%16, %17, %18, %19, %20, %21, %22, %23, %24, %25, %26, %27, %28, %29, %30, %31, "
    "%32, %33, %34, %35, %36, %37, %38, %39, %40, %41, %42, %43, %44, %45, %46, %47, "
    "%48, %49, %50, %51, %52, %53, %54, %55, %56, %57, %58, %59, %60, %61, %62, %63}, "
    "%64, %65, p, 1, 1, 0, %67;\n}\n"
    : "+f"(d[0]), "+f"(d[1]), "+f"(d[2]), "+f"(d[3]), "+f"(d[4]), "+f"(d[5]), "+f"(d[6]), "+f"(d[7]),
      "+f"(d[8]), "+f"(d[9]), "+f"(d[10]), "+f"(d[11]), "+f"(d[12]), "+f"(d[13]), "+f"(d[14]), "+f"(d[15]),
      "+f"(d[16]), "+f"(d[17]), "+f"(d[18]), "+f"(d[19]), "+f"(d[20]), "+f"(d[21]), "+f"(d[22]), "+f"(d[23]),
      "+f"(d[24]), "+f"(d[25]), "+f"(d[26]), "+f"(d[27]), "+f"(d[28]), "+f"(d[29]), "+f"(d[30]), "+f"(d[31]),
      "+f"(d[32]), "+f"(d[33]), "+f"(d[34]), "+f"(d[35]), "+f"(d[36]), "+f"(d[37]), "+f"(d[38]), "+f"(d[39]),
      "+f"(d[40]), "+f"(d[41]), "+f"(d[42]), "+f"(d[43]), "+f"(d[44]), "+f"(d[45]), "+f"(d[46]), "+f"(d[47]),
      "+f"(d[48]), "+f"(d[49]), "+f"(d[50]), "+f"(d[51]), "+f"(d[52]), "+f"(d[53]), "+f"(d[54]), "+f"(d[55]),
      "+f"(d[56]), "+f"(d[57]), "+f"(d[58]), "+f"(d[59]), "+f"(d[60]), "+f"(d[61]), "+f"(d[62]), "+f"(d[63])
    : "l"(descA), "l"(descB), "r"(scaleD), "n"(TB));
}

template<int TB> __device__ __forceinline__ void wgmma_rs_n128(float (&d)[64], uint32_t a0, uint32_t a1, uint32_t a2, uint32_t a3, uint64_t descB, int scaleD) {
  asm volatile("{\n.reg .pred p;\nsetp.ne.b32 p, %69, 0;\n"
    "wgmma.mma_async.sync.aligned.m64n128k16.f32.bf16.bf16 "
    "{%0, %1, %2, %3, %4, %5, %6, %7, %8, %9, %10, %11, %12, %13, %14, %15, "
    "%16, %17, %18, %19, %20, %21, %22, %23, %24, %25, %26, %27, %28, %29, %30, %31, "
    "%32, %33, %34, %35, %36, %37, %38, %39, %40, %41, %42, %43, %44, %45, %46, %47, "
    "%48, %49, %50, %51, %52, %53, %54, %55, %56, %57, %58, %59, %60, %61, %62, %63}, "
    "{%64, %65, %66, %67}, %68, p, 1, 1, %70;\n}\n"
    : "+f"(d[0]), "+f"(d[1]), "+f"(d[2]), "+f"(d[3]), "+f"(d[4]), "+f"(d[5]), "+f"(d[6]), "+f"(d[7]),
      "+f"(d[8]), "+f"(d[9]), "+f"(d[10]), "+f"(d[11]), "+f"(d[12]), "+f"(d[13]), "+f"(d[14]), "+f"(d[15]),
      "+f"(d[16]), "+f"(d[17]), "+f"(d[18]), "+f"(d[19]), "+f"(d[20]), "+f"(d[21]), "+f"(d[22]), "+f"(d[23]),
      "+f"(d[24]), "+f"(d[25]), "+f"(d[26]), "+f"(d[27]), "+f"(d[28]), "+f"(d[29]), "+f"(d[30]), "+f"(d[31]),
      "+f"(d[32]), "+f"(d[33]), "+f"(d[34]), "+f"(d[35]), "+f"(d[36]), "+f"(d[37]), "+f"(d[38]), "+f"(d[39]),
      "+f"(d[40]), "+f"(d[41]), "+f"(d[42]), "+f"(d[43]), "+f"(d[44]), "+f"(d[45]), "+f"(d[46]), "+f"(d[47]),
      "+f"(d[48]), "+f"(d[49]), "+f"(d[50]), "+f"(d[51]), "+f"(d[52]), "+f"(d[53]), "+f"(d[54]), "+f"(d[55]),
      "+f"(d[56]), "+f"(d[57]), "+f"(d[58]), "+f"(d[59]), "+f"(d[60]), "+f"(d[61]), "+f"(d[62]), "+f"(d[63])
    : "r"(a0), "r"(a1), "r"(a2), "r"(a3), "l"(descB), "r"(scaleD), "n"(TB));
}

template<int TB> __device__ __forceinline__ void wgmma_rs_n64(float (&d)[64], uint32_t a0, uint32_t a1, uint32_t a2, uint32_t a3, uint64_t descB, int scaleD) {
  asm volatile("{\n.reg .pred p;\nsetp.ne.b32 p, %37, 0;\n"
    "wgmma.mma_async.sync.aligned.m64n64k16.f32.bf16.bf16 "
    "{%0, %1, %2, %3, %4, %5, %6, %7, %8, %9, %10, %11, %12, %13, %14, %15, "
    "%16, %17, %18, %19, %20, %21, %22, %23, %24, %25, %26, %27, %28, %29, %30, %31}, "
    "{%32, %33, %34, %35}, %36, p, 1, 1, %38;\n}\n"
    : "+f"(d[0]), "+f"(d[1]), "+f"(d[2]), "+f"(d[3]), "+f"(d[4]), "+f"(d[5]), "+f"(d[6]), "+f"(d[7]),
      "+f"(d[8]), "+f"(d[9]), "+f"(d[10]), "+f"(d[11]), "+f"(d[12]), "+f"(d[13]), "+f"(d[14]), "+f"(d[15]),
      "+f"(d[16]), "+f"(d[17]), "+f"(d[18]), "+f"(d[19]), "+f"(d[20]), "+f"(d[21]), "+f"(d[22]), "+f"(d[23]),
      "+f"(d[24]), "+f"(d[25]), "+f"(d[26]), "+f"(d[27]), "+f"(d[28]), "+f"(d[29]), "+f"(d[30]), "+f"(d[31])
    : "r"(a0), "r"(a1), "r"(a2), "r"(a3), "l"(descB), "r"(scaleD), "n"(TB));
}

struct Cur {
  uint32_t o, phase;
  __device__ __forceinline__ void adv() { o += 8; if (o == 8 * NSLOT) { o = 0; phase ^= 1; } }
};

struct Params {
  CUtensorMap ckv, xn, x, wq, wuk, wuv, wo, out;
  const __nv_bfloat16 *px, *w_r, *w_gate, *w_up, *w_down;
  float neg;
};

__device__ __forceinline__ void moe_cta(const Params& P, int q, unsigned ep, uint8_t* smem) {
  float* xs = (float*)smem;
  float* red = xs + DM;
  float* hs = red + 2 * 8 * 344;
  float* sv = hs + 344; int* si = (int*)(sv + 16);
  const int tid = threadIdx.x, lane = tid & 31, warp = tid >> 5;
  if (tid < 16) flag_wait(F_LN + tid, ep * 24);
  __syncthreads();
  float bv = -INFINITY; int bi = 0x7fffffff;
  for (int i = tid; i < SEQ; i += 384) { float v = __ldcg(&g_r[i]); if (v > bv || bi == 0x7fffffff) { bv = v; bi = i; } }
#pragma unroll
  for (int o = 16; o; o >>= 1) {
    float ov = __shfl_xor_sync(~0u, bv, o); int oi = __shfl_xor_sync(~0u, bi, o);
    if (ov > bv || (ov == bv && oi < bi)) { bv = ov; bi = oi; }
  }
  if (lane == 0) { sv[warp] = bv; si[warp] = bi; }
  __syncthreads();
  bv = sv[0]; bi = si[0];
  for (int w = 1; w < 12; w++) { float ov = sv[w]; int oi = si[w]; if (ov > bv || (ov == bv && oi < bi)) { bv = ov; bi = oi; } }
  for (int i = tid; i < DM; i += 384) xs[i] = __bfloat162float(__ldcg(&g_xn[bi * DM + i]));
  __syncthreads();
  const int f0 = q * 344;
  if (tid < 344) {
    const int cg = tid % 43, ksl = tid / 43;
    float ag[8], au[8];
#pragma unroll
    for (int i = 0; i < 8; i++) ag[i] = au[i] = 0.f;
    const __nv_bfloat16* pg = P.w_gate + (size_t)(ksl * 64) * FF + f0 + cg * 8;
    const __nv_bfloat16* pu = P.w_up + (size_t)(ksl * 64) * FF + f0 + cg * 8;
#pragma unroll 8
    for (int k = 0; k < 64; k++) {
      uint4 a = __ldg((const uint4*)(pg + (size_t)k * FF)), b = __ldg((const uint4*)(pu + (size_t)k * FF));
      float xv = xs[ksl * 64 + k];
      ag[0] += xv * bf_lo(a.x); ag[1] += xv * bf_hi(a.x); ag[2] += xv * bf_lo(a.y); ag[3] += xv * bf_hi(a.y);
      ag[4] += xv * bf_lo(a.z); ag[5] += xv * bf_hi(a.z); ag[6] += xv * bf_lo(a.w); ag[7] += xv * bf_hi(a.w);
      au[0] += xv * bf_lo(b.x); au[1] += xv * bf_hi(b.x); au[2] += xv * bf_lo(b.y); au[3] += xv * bf_hi(b.y);
      au[4] += xv * bf_lo(b.z); au[5] += xv * bf_hi(b.z); au[6] += xv * bf_lo(b.w); au[7] += xv * bf_hi(b.w);
    }
#pragma unroll
    for (int i = 0; i < 8; i++) { red[ksl * 344 + cg * 8 + i] = ag[i]; red[(8 + ksl) * 344 + cg * 8 + i] = au[i]; }
  }
  __syncthreads();
  if (tid < 344) {
    float g = 0.f, u = 0.f;
#pragma unroll
    for (int i = 0; i < 8; i++) { g += red[i * 344 + tid]; u += red[(8 + i) * 344 + tid]; }
    g = rbf(g); u = rbf(u);
    g = rbf(g / (1.f + expf(-g)));
    hs[tid] = rbf(g * u);
  }
  __syncthreads();
  {
    const int cg = tid & 63, fs = tid >> 6;
    float ay[8];
#pragma unroll
    for (int i = 0; i < 8; i++) ay[i] = 0.f;
    const __nv_bfloat16* pd = P.w_down + (size_t)f0 * DM + cg * 8;
#pragma unroll 8
    for (int f = fs; f < 344; f += 6) {
      uint4 a = __ldg((const uint4*)(pd + (size_t)f * DM));
      float hv = hs[f];
      ay[0] += hv * bf_lo(a.x); ay[1] += hv * bf_hi(a.x); ay[2] += hv * bf_lo(a.y); ay[3] += hv * bf_hi(a.y);
      ay[4] += hv * bf_lo(a.z); ay[5] += hv * bf_hi(a.z); ay[6] += hv * bf_lo(a.w); ay[7] += hv * bf_hi(a.w);
    }
#pragma unroll
    for (int i = 0; i < 8; i++) red[fs * DM + cg * 8 + i] = ay[i];
  }
  __syncthreads();
  for (int i = tid; i < DM; i += 384) {
    float y = 0.f;
#pragma unroll
    for (int s = 0; s < 6; s++) y += red[s * DM + i];
    g_ypart[q * DM + i] = y;
  }
  if (q == 0 && tid == 0) { g_sel = bi; g_gate = rbf(1.f / (1.f + expf(-bv))); }
  __syncthreads();
  if (tid == 0) { __threadfence(); flag_add(F_MOE); }
}

__device__ __forceinline__ void ln_rows(const Params& P, int row0, int n, int lane) {
  const uint4* px = (const uint4*)(P.px + (size_t)row0 * DM) + lane;
  uint4 na = __ldg(px), nb = __ldg(px + 32);
  for (int i = lane + 8; i < n * 8; i += 32) asm volatile("prefetch.global.L2 [%0];" :: "l"(P.px + (size_t)row0 * DM + i * 64));
#pragma unroll 1
  for (int i = 0; i < n; i++) {
    uint32_t x[8] = {na.x, na.y, na.z, na.w, nb.x, nb.y, nb.z, nb.w};
    if (i + 1 < n) { na = __ldg(px + 64 * (i + 1)); nb = __ldg(px + 64 * (i + 1) + 32); }
    float s0 = 0.f, s1 = 0.f;
#pragma unroll
    for (int k = 0; k < 8; k++) { s0 += bf_lo(x[k]); s1 += bf_hi(x[k]); }
    s0 += s1;
#pragma unroll
    for (int o = 16; o; o >>= 1) s0 += __shfl_xor_sync(~0u, s0, o);
    const float mean = s0 * (1.f / DM);
    s0 = s1 = 0.f;
#pragma unroll
    for (int k = 0; k < 8; k++) { const float d0 = bf_lo(x[k]) - mean, d1 = bf_hi(x[k]) - mean; s0 = fmaf(d0, d0, s0); s1 = fmaf(d1, d1, s1); }
    s0 += s1;
#pragma unroll
    for (int o = 16; o; o >>= 1) s0 += __shfl_xor_sync(~0u, s0, o);
    const uint32_t mb = pack_bf16(mean, mean);
    const float rs = __frcp_rn(rbf(__fsqrt_rn(rbf(rbf(s0 * (1.f / DM)) + 1e-5f))));
#pragma unroll
    for (int k = 0; k < 8; k++) {
      uint32_t d;
      asm("sub.rn.bf16x2 %0, %1, %2;" : "=r"(d) : "r"(x[k]), "r"(mb));
      x[k] = pack_bf16(bf_lo(d) * rs, bf_hi(d) * rs);
    }
    uint4* dst = (uint4*)(g_xn + (size_t)(row0 + i) * DM) + lane;
    dst[0] = make_uint4(x[0], x[1], x[2], x[3]);
    dst[32] = make_uint4(x[4], x[5], x[6], x[7]);
    s0 = s1 = 0.f;
#pragma unroll
    for (int h = 0; h < 2; h++) {
      const uint4 w = __ldg((const uint4*)P.w_r + 32 * h + lane);
      s0 = fmaf(bf_lo(x[4 * h]), bf_lo(w.x), s0); s1 = fmaf(bf_hi(x[4 * h]), bf_hi(w.x), s1);
      s0 = fmaf(bf_lo(x[4 * h + 1]), bf_lo(w.y), s0); s1 = fmaf(bf_hi(x[4 * h + 1]), bf_hi(w.y), s1);
      s0 = fmaf(bf_lo(x[4 * h + 2]), bf_lo(w.z), s0); s1 = fmaf(bf_hi(x[4 * h + 2]), bf_hi(w.z), s1);
      s0 = fmaf(bf_lo(x[4 * h + 3]), bf_lo(w.w), s0); s1 = fmaf(bf_hi(x[4 * h + 3]), bf_hi(w.w), s1);
    }
    s0 += s1;
#pragma unroll
    for (int o = 16; o; o >>= 1) s0 += __shfl_xor_sync(~0u, s0, o);
    if (lane == 0) g_r[row0 + i] = rbf(s0);
  }
}

struct Ctx {
  uint32_t sb;
  uint32_t dlo;
  uint32_t full0;
  uint32_t rel;
  bool rel_pred, warp0;
  uint32_t stg;
  uint32_t stg_full, stg_empty;
  uint32_t stg_phase;
  uint32_t frag_off;
  uint32_t frag_x;
  int w;
  float neg;
  __device__ __forceinline__ void wait(const Cur& c) const { mbar_wait(full0 + c.o, c.phase); }
  __device__ __forceinline__ void release(const Cur& c) const { mbar_arrive_cluster_if(rel + c.o, rel_pred); }
  __device__ __forceinline__ void skip(const Cur& c) const { if (warp0) { wait(c); release(c); } }
  __device__ __forceinline__ uint32_t addr(const Cur& c) const { return sb + c.o * (TILE / 8); }
  __device__ __forceinline__ uint32_t dsc(const Cur& c) const { return dlo + c.o * (TILE / 128); }
  __device__ __forceinline__ void turn_begin() const { bar_sync(1 + w, 256); }
  __device__ __forceinline__ void turn_end() const { bar_arrive(2 - w, 256); }
  __device__ __forceinline__ uint32_t frag(int jj, int hstride) const { return (jj >> 2) * hstride + frag_off + (((jj & 3) * 32) ^ frag_x); }
  template <bool SCALE> __device__ __forceinline__ void stage_out(const float (&d)[64], float s0, float s1) {
    mbar_wait(stg_empty, stg_phase ^ 1);
    stg_phase ^= 1;
#pragma unroll
    for (int jj = 0; jj < 8; jj++) {
      if (SCALE)
        stsm4(stg + frag(jj, 8192), pack_bf16(d[8 * jj] * s0, d[8 * jj + 1] * s0), pack_bf16(d[8 * jj + 2] * s1, d[8 * jj + 3] * s1),
              pack_bf16(d[8 * jj + 4] * s0, d[8 * jj + 5] * s0), pack_bf16(d[8 * jj + 6] * s1, d[8 * jj + 7] * s1));
      else
        stsm4(stg + frag(jj, 8192), pack_bf16(d[8 * jj], d[8 * jj + 1]), pack_bf16(d[8 * jj + 2], d[8 * jj + 3]),
              pack_bf16(d[8 * jj + 4], d[8 * jj + 5]), pack_bf16(d[8 * jj + 6], d[8 * jj + 7]));
    }
  }
  __device__ __forceinline__ void publish() const { fence_async_smem(); mbar_arrive(stg_full); }
};

constexpr float SM_SCALE = 0.08838834764831845f * 1.4426950408889634f;
constexpr float SUM_LIMIT = 1152921504606846976.f;

struct Attn {
  float o[64], s[64];
  uint32_t p[32], q[32];
  float n0, n1;
  float l0, l1;
};

__device__ __forceinline__ void issue_qk(Attn& A, uint32_t d) {
#pragma unroll
  for (int kk = 0; kk < 8; kk++)
    wgmma_rs_n128<0>(A.s, A.q[4 * kk], A.q[4 * kk + 1], A.q[4 * kk + 2], A.q[4 * kk + 3], desc(d + (((kk >> 2) * HALF + (kk & 3) * 32) >> 4)), kk > 0);
  wg_commit();
}
__device__ __forceinline__ void issue_pv(Attn& A, uint32_t d, int acc) {
#pragma unroll
  for (int kk = 0; kk < 8; kk++)
    wgmma_rs_n128<1>(A.o, A.p[4 * kk], A.p[4 * kk + 1], A.p[4 * kk + 2], A.p[4 * kk + 3], desc(d + ((kk * 2048) >> 4)), kk > 0 ? 1 : acc);
  wg_commit();
}
__device__ __forceinline__ void pack_p(Attn& A) {
#pragma unroll
  for (int i = 0; i < 32; i++) A.p[i] = pack_bf16(A.s[2 * i], A.s[2 * i + 1]);
}
__device__ __forceinline__ void block_max(const Attn& A, float& n0, float& n1) {
  float x0 = fmaxf(A.s[0], A.s[1]), x1 = fmaxf(A.s[2], A.s[3]);
  float y0 = fmaxf(A.s[4], A.s[5]), y1 = fmaxf(A.s[6], A.s[7]);
#pragma unroll
  for (int j = 2; j < 16; j += 2) {
    x0 = fmaxf(x0, fmaxf(A.s[4 * j], A.s[4 * j + 1])); x1 = fmaxf(x1, fmaxf(A.s[4 * j + 2], A.s[4 * j + 3]));
    y0 = fmaxf(y0, fmaxf(A.s[4 * j + 4], A.s[4 * j + 5])); y1 = fmaxf(y1, fmaxf(A.s[4 * j + 6], A.s[4 * j + 7]));
  }
  x0 = fmaxf(x0, y0); x1 = fmaxf(x1, y1);
  x0 = fmaxf(x0, __shfl_xor_sync(~0u, x0, 1)); x1 = fmaxf(x1, __shfl_xor_sync(~0u, x1, 1));
  x0 = fmaxf(x0, __shfl_xor_sync(~0u, x0, 2)); x1 = fmaxf(x1, __shfl_xor_sync(~0u, x1, 2));
  n0 = -x0 * SM_SCALE; n1 = -x1 * SM_SCALE;
}
template <int J0, int J1> __device__ __forceinline__ void exp_cols(Attn& A, float (&a)[4]) {
#pragma unroll
  for (int j = J0; j < J1; j++) {
    A.s[4 * j] = ex2(fmaf(A.s[4 * j], SM_SCALE, A.n0)); A.s[4 * j + 1] = ex2(fmaf(A.s[4 * j + 1], SM_SCALE, A.n0));
    A.s[4 * j + 2] = ex2(fmaf(A.s[4 * j + 2], SM_SCALE, A.n1)); A.s[4 * j + 3] = ex2(fmaf(A.s[4 * j + 3], SM_SCALE, A.n1));
    if (j == 0) { a[0] = A.s[0]; a[1] = A.s[1]; a[2] = A.s[2]; a[3] = A.s[3]; }
    else { a[0] += A.s[4 * j]; a[1] += A.s[4 * j + 1]; a[2] += A.s[4 * j + 2]; a[3] += A.s[4 * j + 3]; }
  }
}
__device__ __forceinline__ void pin(float v, float neg, uint32_t addr) {
  asm volatile("{\n.reg .pred p;\nsetp.lt.f32 p, %0, %2;\n@p mbarrier.arrive.shared::cta.b64 _, [%1];\n}" :: "f"(v), "r"(addr), "f"(neg) : "memory");
}
__device__ __forceinline__ void causal_mask(Attn& A, int rel) {
#pragma unroll
  for (int j = 0; j < 16; j++) {
    if (8 * j > rel) A.s[4 * j] = -INFINITY;
    if (8 * j + 1 > rel) A.s[4 * j + 1] = -INFINITY;
    if (8 * j > rel + 8) A.s[4 * j + 2] = -INFINITY;
    if (8 * j + 1 > rel + 8) A.s[4 * j + 3] = -INFINITY;
  }
}
__device__ __forceinline__ void finish_item(Ctx& C, Attn& A, float l0, float l1) {
  l0 += __shfl_xor_sync(~0u, l0, 1); l1 += __shfl_xor_sync(~0u, l1, 1);
  l0 += __shfl_xor_sync(~0u, l0, 2); l1 += __shfl_xor_sync(~0u, l1, 2);
  C.stage_out<true>(A.o, __fdividef(1.f, l0), __fdividef(1.f, l1));
}
__device__ __forceinline__ void redo_block(Attn& A, const uint8_t* ktile, bool diag, int rel) {
  const int lane = threadIdx.x & 31;
  const uint8_t* kp = ktile + (lane >> 2) * 128 + (lane & 3) * 4;
  const int sw = (lane >> 2) * 16;
#pragma unroll
  for (int j = 0; j < 16; j++) {
    float c0 = 0.f, c1 = 0.f, c2 = 0.f, c3 = 0.f;
#pragma unroll
    for (int kk = 0; kk < 8; kk++) {
      const uint32_t b0 = __ldcg((const uint32_t*)(kp + j * 1024 + (kk >> 2) * HALF + (((kk & 3) * 32) ^ sw)));
      const uint32_t b1 = __ldcg((const uint32_t*)(kp + j * 1024 + (kk >> 2) * HALF + (((kk & 3) * 32 + 16) ^ sw)));
      asm volatile("mma.sync.aligned.m16n8k16.row.col.f32.bf16.bf16.f32 {%0, %1, %2, %3}, {%4, %5, %6, %7}, {%8, %9}, {%0, %1, %2, %3};"
                   : "+f"(c0), "+f"(c1), "+f"(c2), "+f"(c3)
                   : "r"(A.q[4 * kk]), "r"(A.q[4 * kk + 1]), "r"(A.q[4 * kk + 2]), "r"(A.q[4 * kk + 3]), "r"(b0), "r"(b1) : "memory");
    }
    A.s[4 * j] = c0; A.s[4 * j + 1] = c1; A.s[4 * j + 2] = c2; A.s[4 * j + 3] = c3;
  }
  if (diag) causal_mask(A, rel);
  float n0, n1, a[4];
  block_max(A, n0, n1);
  n0 = fminf(n0, A.n0); n1 = fminf(n1, A.n1);
  const float c0 = ex2(n0 - A.n0), c1 = ex2(n1 - A.n1);
  A.n0 = n0; A.n1 = n1;
  exp_cols<0, 16>(A, a);
  A.l0 = fmaf(A.l0, c0, a[0] + a[1]); A.l1 = fmaf(A.l1, c1, a[2] + a[3]);
#pragma unroll
  for (int j = 0; j < 16; j++) { A.o[4 * j] *= c0; A.o[4 * j + 1] *= c0; A.o[4 * j + 2] *= c1; A.o[4 * j + 3] *= c1; }
  pack_p(A);
}
template <bool HAS_PREV> __device__ __forceinline__ void item_begin(Ctx& C, Attn& A, Cur& cur, bool skip, int pv_acc, bool pub, bool diag, int rel) {
  Cur cq, ck, cv, cs;
  if (HAS_PREV && skip) { C.skip(cur); cur.adv(); cv = cur; cur.adv(); }
  cq = cur; cur.adv();
  ck = cur; cur.adv();
  if (HAS_PREV) { cs = cur; cur.adv(); if (!skip) cv = cs; }
  C.wait(cq);
  {
    const uint32_t qa = C.addr(cq) + C.w * 8192;
#pragma unroll
    for (int jj = 0; jj < 8; jj++) ldsm4(qa + C.frag(jj, HALF), A.q[4 * jj], A.q[4 * jj + 1], A.q[4 * jj + 2], A.q[4 * jj + 3]);
  }
  C.wait(ck);
  C.turn_begin();
  wg_fence();
  issue_qk(A, C.dsc(ck));
  if (HAS_PREV) { C.wait(cv); wg_fence(); issue_pv(A, C.dsc(cv), pv_acc); }
  C.turn_end();
  if (pub) C.publish();
  if (HAS_PREV) wg_wait<1>(); else wg_wait<0>();
  reg_fence(A.s);
  C.release(cq); C.release(ck);
  if (diag) causal_mask(A, rel);
  block_max(A, A.n0, A.n1);
  if (HAS_PREV) {
    wg_wait<0>();
    reg_fence(A.o);
    C.release(cv);
    finish_item(C, A, A.l0, A.l1);
  }
  float a[4];
  exp_cols<0, 16>(A, a);
  A.l0 = a[0] + a[1]; A.l1 = a[2] + a[3];
  pack_p(A);
  if (HAS_PREV && skip) C.skip(cs);
}
__device__ __forceinline__ void item_step(Ctx& C, Attn& A, Cur& cur, int pv_acc, bool pub, bool diag, int rel, const uint8_t* ktile) {
  const Cur ck = cur; cur.adv();
  const Cur cv = cur; cur.adv();
  C.wait(ck);
  C.turn_begin();
  wg_fence();
  issue_qk(A, C.dsc(ck));
  C.wait(cv);
  wg_fence();
  issue_pv(A, C.dsc(cv), pv_acc);
  C.turn_end();
  if (pub) C.publish();
  wg_wait<1>();
  reg_fence(A.s);
  C.release(ck);
  if (diag) causal_mask(A, rel);
  float a[4];
  exp_cols<0, 8>(A, a);
  pin((a[0] + a[1]) + (a[2] + a[3]), C.neg, C.stg_full);
  wg_wait<0>();
  reg_fence(A.o);
  C.release(cv);
  exp_cols<8, 16>(A, a);
  pack_p(A);
  const float b0 = a[0] + a[1], b1 = a[2] + a[3];
  if (__builtin_expect(__any_sync(~0u, !(b0 + b1 <= SUM_LIMIT)), 0)) redo_block(A, ktile, diag, rel);
  else { A.l0 += b0; A.l1 += b1; }
}

template <bool LOAD_A> __device__ __forceinline__ void proj_unit(Ctx& C, Cur& cur, uint32_t (&a)[128], float (&acc)[64], bool pub) {
#pragma unroll
  for (int i = 0; i < 4; i++) {
    Cur ca = cur;
    if (LOAD_A) {
      cur.adv();
      C.wait(ca);
      const uint32_t aa = C.addr(ca) + C.w * 8192;
#pragma unroll
      for (int jj = 0; jj < 8; jj++) ldsm4(aa + C.frag(jj, HALF), a[32 * i + 4 * jj], a[32 * i + 4 * jj + 1], a[32 * i + 4 * jj + 2], a[32 * i + 4 * jj + 3]);
    }
    const Cur cb = cur; cur.adv();
    C.wait(cb);
    C.turn_begin();
    wg_fence();
    const uint32_t d = C.dsc(cb);
#pragma unroll
    for (int kk = 0; kk < 8; kk++)
      wgmma_rs_n128<1>(acc, a[32 * i + 4 * kk], a[32 * i + 4 * kk + 1], a[32 * i + 4 * kk + 2], a[32 * i + 4 * kk + 3], desc(d + ((kk * 2048) >> 4)), (i | kk) > 0);
    wg_commit();
    C.turn_end();
    if (i == 0 && pub) C.publish();
    wg_wait<0>();
    reg_fence(acc);
    if (LOAD_A) C.release(ca);
    C.release(cb);
  }
  C.stage_out<false>(acc, 1.f, 1.f);
}

__global__ void __cluster_dims__(2, 1, 1) __launch_bounds__(384, 1) fused_kernel(const __grid_constant__ Params P) {
  extern __shared__ uint8_t smem_raw[];
  uint8_t* smem = smem_raw + ((1024 - (smem_u32(smem_raw) & 1023)) & 1023);
  const int tid = threadIdx.x;
  const int c = blockIdx.x >> 1, r = blockIdx.x & 1;
  const unsigned ep = g_epoch[blockIdx.x] + 1;
  if (c >= 64) {
    moe_cta(P, blockIdx.x - 128, ep, smem);
    if (tid == 0) g_epoch[blockIdx.x] = ep;
    return;
  }
  const uint32_t sb = smem_u32(smem);
  const uint32_t full0 = sb + SMEM_BAR, empty0 = full0 + 8 * NSLOT, stgf0 = empty0 + 8 * NSLOT, stge0 = stgf0 + 16;
  if (tid == 0) {
    for (int i = 0; i < NSLOT; i++) { mbar_init(full0 + 8 * i, 1); mbar_init(empty0 + 8 * i, 4); }
    for (int i = 0; i < 2; i++) { mbar_init(stgf0 + 8 * i, 128); mbar_init(stge0 + 8 * i, 1); }
    asm volatile("fence.mbarrier_init.release.cluster;" ::: "memory");
  }
  asm volatile("barrier.cluster.arrive.aligned;\nbarrier.cluster.wait.aligned;" ::: "memory");

  const int rp = c & 7, g = c >> 3;
  const int rb = 2 * rp + r;
  const int ma = rp & 3, hb = rp >> 2;
  const int j3 = c & 15, ks = c >> 5, ncol = 2 * ((c >> 4) & 1) + r;
  const int wg = __shfl_sync(~0u, tid >> 7, 0);

  if (wg == 0) {
    asm volatile("setmaxnreg.dec.sync.aligned.u32 40;");
    const int warp = tid >> 5;
    if (warp == 0) {
      if (tid == 0) {
        Cur cur{0, 0};
        uint32_t dst, bar;
        auto acquire = [&]() {
          mbar_wait(empty0 + cur.o, cur.phase ^ 1);
          dst = sb + cur.o * (TILE / 8); bar = full0 + cur.o;
          mbar_expect(bar, TILE);
          cur.adv();
        };
        for (int u = 0; u < 12; u++) {
          const CUtensorMap* wm = u >= 8 ? &P.wq : ((u & 1) ? &P.wuv : &P.wuk);
          const CUtensorMap* am = u >= 8 ? &P.xn : &P.ckv;
          const int head = 4 * g + (u >= 8 ? u - 8 : u >> 1);
          if (u == 8) { flag_wait(F_LN + rb, ep * 24); fence_async_all(); }
          for (int i = 0; i < 4; i++) {
            if ((u & 7) == 0) {
              acquire();
              tma_load(dst, am, 128 * i, rb * 128, bar);
              tma_load(dst + HALF, am, 128 * i + 64, rb * 128, bar);
            }
            acquire();
            tma_load_mc(dst + r * HALF, wm, head * 128 + 64 * r, 128 * i, bar);
          }
        }
        const uint8_t* prev_v = nullptr;
        for (int it = 0; it < 4; it++) {
          const int head = 4 * g + (it & 2) + hb;
          const int m = (it & 1) ? ma : 7 - ma;
          const int j = 2 * m + (r ^ (it & 1));
          if (!(it & 1)) { flag_wait(F_HEAD + head, ep * 32); fence_async_all(); }
          acquire();
          bulk_load(dst, g_qkv + (size_t)(head * 16 + j) * TILE, TILE, bar);
          for (int b = 0; b <= 2 * m + 1; b++) {
            acquire();
            bulk_load_mc(dst + r * HALF, g_qkv + (size_t)((NH + head) * 16 + b) * TILE + r * HALF, HALF, bar);
            if (prev_v) { acquire(); bulk_load_mc(dst + r * HALF, prev_v, HALF, bar); }
            prev_v = g_qkv + (size_t)((2 * NH + head) * 16 + b) * TILE + r * HALF;
          }
        }
        acquire(); bulk_load_mc(dst + r * HALF, prev_v, HALF, bar);
        for (int t = 0; t < 16; t++) {
          const int head = 16 * ks + 4 * ((t & 7) >> 1) + 2 * (t >> 3) + (t & 1);
          acquire();
          tma_load(dst + ks * HALF, &P.wo, ncol * 128, head * 128, bar);
          tma_load(dst + (ks ^ 1) * HALF, &P.wo, ncol * 128 + 64, head * 128, bar);
          if ((t & 7) == 0) { flag_wait(F_CTX + j3 * 4 + ks * 2 + (t >> 3), ep * 16); fence_async_all(); }
          acquire();
          bulk_load_mc(dst + r * HALF, g_ctx + (size_t)(head * 16 + j3) * TILE + r * HALF, HALF, bar);
        }
        flag_wait(F_LN + j3, ep * 24);
        flag_wait(F_MOE, ep * 4);
        fence_async_all();
        acquire();
        tma_load(dst, &P.x, ncol * 128 + 64 * ks, j3 * 128, bar);
        tma_load(dst + HALF, &P.xn, ncol * 128 + 64 * ks, j3 * 128, bar);
        for (int i = 0; i < NSLOT; i++) { mbar_wait(empty0 + cur.o, cur.phase ^ 1); cur.adv(); }
        g_epoch[blockIdx.x] = ep;
      }
    } else {
      ln_rows(P, rb * 128 + 16 * g + 3 * (warp - 1), warp < 3 ? 3 : 10, tid & 31);
      __syncwarp();
      TLX(12 + warp);
      if ((tid & 31) == 0) { __threadfence(); fence_async_all(); flag_add(F_LN + rb); }
      if (warp < 3 && (tid & 31) == 0) {
        const int w = warp - 1;
        const uint32_t stg = sb + SMEM_STG + w * HALF;
        for (int job = 0; job < 17; job++) {
          mbar_wait(stgf0 + 8 * w, job & 1);
          int flag = -1;
          if (job < 16) {
            uint8_t* d;
            if (job < 12) {
              const int head = 4 * g + (job >= 8 ? job - 8 : job >> 1);
              const int kind = job >= 8 ? 0 : 1 + (job & 1);
              d = g_qkv + (size_t)((kind * NH + head) * 16 + rb) * TILE;
              if (job >= 8) flag = F_HEAD + head;
            } else {
              const int it = job - 12;
              const int head = 4 * g + (it & 2) + hb;
              const int m = (it & 1) ? ma : 7 - ma;
              const int j = 2 * m + (r ^ (it & 1));
              d = g_ctx + (size_t)(head * 16 + j) * TILE;
              flag = F_CTX + j * 4 + (g >> 2) * 2 + (it >> 1);
            }
            bulk_store(d + w * 8192, stg, 8192);
            bulk_store(d + HALF + w * 8192, stg + 8192, 8192);
          } else {
            tma_store(&P.out, ncol * 128 + 64 * ks, j3 * 128 + 64 * w, stg);
          }
          asm volatile("cp.async.bulk.commit_group;" ::: "memory");
          asm volatile("cp.async.bulk.wait_group.read 0;" ::: "memory");
          mbar_arrive(stge0 + 8 * w);
          if (job >= 8) asm volatile("cp.async.bulk.wait_group 0;" ::: "memory");
          if (flag >= 0) { fence_async_all(); flag_add(flag); }
          if (w == 1 && job >= 8 && job < 12) TLX(28 + job - 8);
        }
      }
    }
  } else {
    asm volatile("setmaxnreg.inc.sync.aligned.u32 232;");
    const int t = tid & 127, lane = tid & 31, wi = t >> 5;
    Ctx C;
    C.neg = P.neg; C.sb = sb; C.dlo = desc_lo(sb); C.full0 = full0; C.w = wg - 1;
    asm("mapa.shared::cluster.u32 %0, %1, %2;" : "=r"(C.rel) : "r"(empty0), "r"(lane & 1));
    C.rel_pred = t < 2;
    C.warp0 = __shfl_sync(~0u, wi, 0) == 0;
    C.stg = sb + SMEM_STG + C.w * HALF;
    C.stg_full = stgf0 + 8 * C.w; C.stg_empty = stge0 + 8 * C.w; C.stg_phase = 0;
    C.frag_off = (16 * wi + (lane & 15)) * 128;
    C.frag_x = ((lane >> 4) ^ (lane & 7)) * 16;
    TL(C.w * 16 + 0);
    if (C.w == 1) bar_arrive(1, 256);
    Cur cur{0, 0};
    TL(C.w * 16 + 1);
    {
      uint32_t a[128];
      float acc[64];
#pragma unroll 1
      for (int half = 0; half < 2; half++) {
        proj_unit<true>(C, cur, a, acc, half);
        if (half == 0) TL(C.w * 16 + 2);
#pragma unroll 1
        for (int u = half ? 5 : 1; u < 8; u++) proj_unit<false>(C, cur, a, acc, true);
      }
    }
    TL(C.w * 16 + 3);
    {
      Attn A;
      const int rel = 64 * C.w + 16 * wi + (lane >> 2) - 2 * (lane & 3);
      A.l0 = A.l1 = 0.f;
      int pv_acc = 0;
      bool skip = false, pub = true;
#pragma unroll 1
      for (int it = 0; it < 4; it++) {
        const int m = (it & 1) ? ma : 7 - ma;
        const int role = r ^ (it & 1);
        const int j = 2 * m + role;
        if (it == 0) item_begin<false>(C, A, cur, false, 0, true, j == 0, rel);
        else item_begin<true>(C, A, cur, skip, pv_acc, pub, j == 0, rel);
        pv_acc = 0; pub = it > 0; skip = role == 0;
        const uint8_t* kt = g_qkv + (size_t)((NH + 4 * g + (it & 2) + hb) * 16) * TILE;
#pragma unroll 1
        for (int b = 1; b <= j; b++) { item_step(C, A, cur, pv_acc, pub, b == j, rel, kt + (size_t)b * TILE); pv_acc = 1; pub = false; }
        TL(C.w * 16 + 4 + it);
      }
      if (skip) { C.skip(cur); cur.adv(); }
      const Cur cv = cur; cur.adv();
      C.wait(cv);
      C.turn_begin();
      wg_fence();
      issue_pv(A, C.dsc(cv), pv_acc);
      C.turn_end();
      if (pub) C.publish();
      wg_wait<0>();
      reg_fence(A.o);
      C.release(cv);
      finish_item(C, A, A.l0, A.l1);
      C.publish();
      if (skip) { C.skip(cur); cur.adv(); }
      if (C.w == 0) C.turn_begin();
    }
    TL(C.w * 16 + 8);
    {
      float acc[64];
      Cur pb = cur, pa = cur;
#pragma unroll 1
      for (int h = 0; h < 16; h++) {
        const Cur cb = cur; cur.adv();
        const Cur ca = cur; cur.adv();
        C.wait(cb); C.wait(ca);
        wg_fence();
        const uint32_t da = C.dsc(ca) + C.w * 512, db = C.dsc(cb);
#pragma unroll
        for (int kk = 0; kk < 8; kk++)
          wgmma_ss_n128<1>(acc, desc(da + (((kk >> 2) * HALF + (kk & 3) * 32) >> 4)), desc(db + ((kk * 2048) >> 4)), kk > 0 ? 1 : h);
        wg_commit();
        wg_wait<1>();
        if (h > 0) { C.release(pb); C.release(pa); }
        pb = cb; pa = ca;
      }
      wg_wait<0>();
      reg_fence(acc);
      C.release(pb); C.release(pa);
      TL(C.w * 16 + 9);
      float4* mine = g_part + (size_t)blockIdx.x * 2048 + C.w * 1024 + t;
      const float4* theirs = g_part + (size_t)(blockIdx.x ^ 64) * 2048 + C.w * 1024 + t;
#pragma unroll
      for (int i = 0; i < 8; i++) __stcg(mine + i * 128, make_float4(acc[32 + 4 * i], acc[33 + 4 * i], acc[34 + 4 * i], acc[35 + 4 * i]));
      bar_sync(4 + C.w, 128);
      if (t == 0) {
        __threadfence();
        flag_add(F_PART + blockIdx.x * 2 + C.w);
        flag_wait(F_PART + (blockIdx.x ^ 64) * 2 + C.w, ep);
      }
      const Cur cr = cur;
      C.wait(cr);
      uint32_t xr[16], nr[16];
      const uint32_t xa = C.addr(cr) + C.w * 8192;
#pragma unroll
      for (int jj = 0; jj < 4; jj++) {
        ldsm4(xa + C.frag(jj, 0), xr[4 * jj], xr[4 * jj + 1], xr[4 * jj + 2], xr[4 * jj + 3]);
        ldsm4(xa + HALF + C.frag(jj, 0), nr[4 * jj], nr[4 * jj + 1], nr[4 * jj + 2], nr[4 * jj + 3]);
      }
      const int sel = __ldcg(&g_sel);
      const int row0 = j3 * 128 + 64 * C.w + 16 * wi + (lane >> 2);
      if (sel == row0 || sel == row0 + 8) {
        const float gate = __ldcg(&g_gate);
        const float* yp = g_ypart + ncol * 128 + 64 * ks + 2 * (lane & 3);
#pragma unroll
        for (int j = 0; j < 8; j++) {
          float y0 = 0.f, y1 = 0.f;
#pragma unroll
          for (int q = 0; q < 4; q++) { y0 += __ldcg(yp + q * DM + 8 * j); y1 += __ldcg(yp + q * DM + 8 * j + 1); }
          y0 = rbf(rbf(y0) * gate); y1 = rbf(rbf(y1) * gate);
          if (sel == row0) nr[2 * j] = pack_bf16(bf_lo(nr[2 * j]) + y0, bf_hi(nr[2 * j]) + y1);
          else nr[2 * j + 1] = pack_bf16(bf_lo(nr[2 * j + 1]) + y0, bf_hi(nr[2 * j + 1]) + y1);
        }
      }
      bar_sync(4 + C.w, 128);
      C.release(cr);
      TL(C.w * 16 + 10);
#pragma unroll
      for (int i = 0; i < 8; i++) {
        const float4 v = __ldcg(theirs + i * 128);
        acc[4 * i] += v.x; acc[4 * i + 1] += v.y; acc[4 * i + 2] += v.z; acc[4 * i + 3] += v.w;
      }
      uint32_t o[16];
#pragma unroll
      for (int i = 0; i < 16; i++)
        o[i] = pack_bf16(rbf(bf_lo(xr[i]) + rbf(acc[2 * i])) + bf_lo(nr[i]), rbf(bf_hi(xr[i]) + rbf(acc[2 * i + 1])) + bf_hi(nr[i]));
      mbar_wait(C.stg_empty, C.stg_phase ^ 1);
#pragma unroll
      for (int jj = 0; jj < 4; jj++) stsm4(C.stg + C.frag(jj, 0), o[4 * jj], o[4 * jj + 1], o[4 * jj + 2], o[4 * jj + 3]);
      fence_async_smem();
      mbar_arrive(C.stg_full);
      TL(C.w * 16 + 11);
    }
  }
}

typedef CUresult (*EncodeFn)(CUtensorMap*, CUtensorMapDataType, cuuint32_t, void*, const cuuint64_t*, const cuuint64_t*,
                             const cuuint32_t*, const cuuint32_t*, CUtensorMapInterleave, CUtensorMapSwizzle,
                             CUtensorMapL2promotion, CUtensorMapFloatOOBfill);

void make_map(EncodeFn fn, CUtensorMap* m, const void* ptr, uint64_t cols, uint64_t rows, uint32_t box_rows) {
  cuuint64_t dims[2] = {cols, rows};
  cuuint64_t strides[1] = {cols * 2};
  cuuint32_t box[2] = {64, box_rows};
  cuuint32_t es[2] = {1, 1};
  fn(m, CU_TENSOR_MAP_DATA_TYPE_BFLOAT16, 2, const_cast<void*>(ptr), dims, strides, box, es, CU_TENSOR_MAP_INTERLEAVE_NONE,
     CU_TENSOR_MAP_SWIZZLE_128B, CU_TENSOR_MAP_L2_PROMOTION_L2_128B, CU_TENSOR_MAP_FLOAT_OOB_FILL_NONE);
}

}

extern "C" void kernel_launch(void* const* d_in, const int* in_sizes, int n_in, void* d_out, int out_size) {
  static EncodeFn fn = nullptr;
  static void* xn_ptr = nullptr;
  if (!fn) {
    void* f = nullptr;
    cudaDriverEntryPointQueryResult qr;
    cudaGetDriverEntryPoint("cuTensorMapEncodeTiled", &f, cudaEnableDefault, &qr);
    fn = (EncodeFn)f;
    cudaGetSymbolAddress(&xn_ptr, g_xn);
    cudaFuncSetAttribute(fused_kernel, cudaFuncAttributeMaxDynamicSharedMemorySize, SMEM_TOTAL);
  }
  Params P;
  make_map(fn, &P.x, d_in[0], DM, SEQ, 128);
  make_map(fn, &P.ckv, d_in[1], DM, SEQ, 128);
  make_map(fn, &P.xn, xn_ptr, DM, SEQ, 128);
  make_map(fn, &P.wq, d_in[2], NH * 128, DM, 128);
  make_map(fn, &P.wuk, d_in[3], NH * 128, DM, 128);
  make_map(fn, &P.wuv, d_in[4], NH * 128, DM, 128);
  make_map(fn, &P.wo, d_in[5], DM, NH * 128, 128);
  make_map(fn, &P.out, d_out, DM, SEQ, 64);
  P.neg = -1.f;
  P.px = (const __nv_bfloat16*)d_in[0];
  P.w_r = (const __nv_bfloat16*)d_in[7];
  P.w_gate = (const __nv_bfloat16*)d_in[8];
  P.w_up = (const __nv_bfloat16*)d_in[9];
  P.w_down = (const __nv_bfloat16*)d_in[10];
  fused_kernel<<<NCTA, 384, SMEM_TOTAL>>>(P);
}
```

```cpp
#include <cuda_runtime.h>
#include <cuda_bf16.h>
#include <cuda.h>
#include <stdint.h>

namespace {

constexpr int SEQ = 2048, DM = 512, NH = 32, FF = 1376;
constexpr int NSLOT = 6;
constexpr int TILE = 32768;
constexpr int HALF = 16384;
constexpr int SMEM_STG = NSLOT * TILE;
constexpr int SMEM_BAR = SMEM_STG + 32768;
constexpr int SMEM_TOTAL = SMEM_BAR + 256 + 1024;
constexpr int NCTA = 132;
constexpr int SPIN_LIMIT = 1 << 22;

constexpr int F_LN = 0;
constexpr int F_HEAD = 16;
constexpr int F_CTX = 48;
constexpr int F_PART = 112;
constexpr int F_MOE = 368;
constexpr int F_COUNT = 369;

__device__ __align__(1024) __nv_bfloat16 g_xn[SEQ * DM];
__device__ float g_r[SEQ];
__device__ __align__(1024) uint8_t g_qkv[3ull * NH * 16 * TILE];
__device__ __align__(1024) uint8_t g_ctx[1ull * NH * 16 * TILE];
__device__ __align__(1024) float4 g_part[128 * 256 * 8];
__device__ float g_ypart[4 * DM];
__device__ int g_sel;
__device__ float g_gate;
__device__ unsigned g_flags[F_COUNT * 32];
__device__ unsigned g_epoch[NCTA];
#define TL(i)
#define TLX(i)

__device__ __forceinline__ uint32_t smem_u32(const void* p) { return (uint32_t)__cvta_generic_to_shared(p); }
__device__ __forceinline__ void mbar_init(uint32_t bar, int cnt) { asm volatile("mbarrier.init.shared::cta.b64 [%0], %1;" :: "r"(bar), "r"(cnt)); }
__device__ __forceinline__ void mbar_arrive(uint32_t bar) { asm volatile("mbarrier.arrive.shared::cta.b64 _, [%0];" :: "r"(bar) : "memory"); }
__device__ __forceinline__ void mbar_arrive_cluster_if(uint32_t bar, bool pred) {
  asm volatile("{\n.reg .pred p;\nsetp.ne.b32 p, %1, 0;\n@p mbarrier.arrive.shared::cluster.b64 _, [%0];\n}" :: "r"(bar), "r"((int)pred) : "memory");
}
__device__ __forceinline__ void mbar_expect(uint32_t bar, int bytes) { asm volatile("mbarrier.arrive.expect_tx.shared::cta.b64 _, [%0], %1;" :: "r"(bar), "r"(bytes) : "memory"); }
__device__ __forceinline__ void mbar_wait(uint32_t bar, uint32_t parity) {
  asm volatile("{\n.reg .pred p, q;\n.reg .b32 n;\n"
               "mbarrier.try_wait.parity.shared::cta.b64 p, [%0], %1;\n@p bra DONE;\nmov.b32 n, 0;\n"
               "LOOP:\nmbarrier.try_wait.parity.shared::cta.b64 p, [%0], %1;\nadd.s32 n, n, 1;\nsetp.lt.s32 q, n, %2;\n@p bra DONE;\n@q bra LOOP;\n"
               "DONE:\n}" :: "r"(bar), "r"(parity), "n"(SPIN_LIMIT) : "memory");
}
__device__ __forceinline__ void bulk_load(uint32_t dst, const void* src, int bytes, uint32_t bar) {
  asm volatile("cp.async.bulk.shared::cluster.global.mbarrier::complete_tx::bytes [%0], [%1], %2, [%3];" :: "r"(dst), "l"(src), "r"(bytes), "r"(bar) : "memory");
}
__device__ __forceinline__ void bulk_load_mc(uint32_t dst, const void* src, int bytes, uint32_t bar) {
  asm volatile("cp.async.bulk.shared::cluster.global.mbarrier::complete_tx::bytes.multicast::cluster [%0], [%1], %2, [%3], %4;" :: "r"(dst), "l"(src), "r"(bytes), "r"(bar), "h"((uint16_t)3) : "memory");
}
__device__ __forceinline__ void tma_load(uint32_t dst, const CUtensorMap* map, int c0, int c1, uint32_t bar) {
  asm volatile("cp.async.bulk.tensor.2d.shared::cluster.global.mbarrier::complete_tx::bytes [%0], [%1, {%3, %4}], [%2];" :: "r"(dst), "l"(map), "r"(bar), "r"(c0), "r"(c1) : "memory");
}
__device__ __forceinline__ void tma_load_mc(uint32_t dst, const CUtensorMap* map, int c0, int c1, uint32_t bar) {
  asm volatile("cp.async.bulk.tensor.2d.shared::cluster.global.mbarrier::complete_tx::bytes.multicast::cluster [%0], [%1, {%3, %4}], [%2], %5;" :: "r"(dst), "l"(map), "r"(bar), "r"(c0), "r"(c1), "h"((uint16_t)3) : "memory");
}
__device__ __forceinline__ void bulk_store(void* dst, uint32_t src, int bytes) {
  asm volatile("cp.async.bulk.global.shared::cta.bulk_group [%0], [%1], %2;" :: "l"(dst), "r"(src), "r"(bytes) : "memory");
}
__device__ __forceinline__ void tma_store(const CUtensorMap* map, int c0, int c1, uint32_t src) {
  asm volatile("cp.async.bulk.tensor.2d.global.shared::cta.bulk_group [%0, {%2, %3}], [%1];" :: "l"(map), "r"(src), "r"(c0), "r"(c1) : "memory");
}
__device__ __forceinline__ void fence_async_smem() { asm volatile("fence.proxy.async.shared::cta;" ::: "memory"); }
__device__ __forceinline__ void fence_async_all() { asm volatile("fence.proxy.async;" ::: "memory"); }
__device__ __forceinline__ void flag_add(int f) { asm volatile("red.release.gpu.global.add.u32 [%0], 1;" :: "l"(&g_flags[f * 32]) : "memory"); }
__device__ __forceinline__ void flag_wait(int f, unsigned target) {
  const unsigned* p = &g_flags[f * 32];
  for (int n = 0; n < SPIN_LIMIT; ++n) {
    unsigned v;
    asm volatile("ld.acquire.gpu.global.u32 %0, [%1];" : "=r"(v) : "l"(p) : "memory");
    if ((int)(v - target) >= 0) break;
  }
}
__device__ __forceinline__ void bar_sync(int id, int n) { asm volatile("bar.sync %0, %1;" :: "r"(id), "r"(n) : "memory"); }
__device__ __forceinline__ void bar_arrive(int id, int n) { asm volatile("bar.arrive %0, %1;" :: "r"(id), "r"(n) : "memory"); }
__device__ __forceinline__ void wg_fence() { asm volatile("wgmma.fence.sync.aligned;" ::: "memory"); }
__device__ __forceinline__ void wg_commit() { asm volatile("wgmma.commit_group.sync.aligned;" ::: "memory"); }
template <int N> __device__ __forceinline__ void wg_wait() { asm volatile("wgmma.wait_group.sync.aligned %0;" :: "n"(N) : "memory"); }
template <int N> __device__ __forceinline__ void reg_fence(float (&d)[N]) {
#pragma unroll
  for (int i = 0; i < N; i++) asm volatile("" : "+f"(d[i]) :: "memory");
}
__device__ __forceinline__ void ldsm4(uint32_t addr, uint32_t& r0, uint32_t& r1, uint32_t& r2, uint32_t& r3) {
  asm volatile("ldmatrix.sync.aligned.m8n8.x4.shared.b16 {%0, %1, %2, %3}, [%4];" : "=r"(r0), "=r"(r1), "=r"(r2), "=r"(r3) : "r"(addr) : "memory");
}
__device__ __forceinline__ void stsm4(uint32_t addr, uint32_t r0, uint32_t r1, uint32_t r2, uint32_t r3) {
  asm volatile("stmatrix.sync.aligned.m8n8.x4.shared.b16 [%0], {%1, %2, %3, %4};" :: "r"(addr), "r"(r0), "r"(r1), "r"(r2), "r"(r3) : "memory");
}
__device__ __forceinline__ uint32_t pack_bf16(float lo, float hi) {
  uint32_t r; asm("cvt.rn.bf16x2.f32 %0, %1, %2;" : "=r"(r) : "f"(hi), "f"(lo)); return r;
}
__device__ __forceinline__ float ex2(float x) { float y; asm("ex2.approx.ftz.f32 %0, %1;" : "=f"(y) : "f"(x)); return y; }
__device__ __forceinline__ float bf_lo(uint32_t v) { return __uint_as_float(v << 16); }
__device__ __forceinline__ float bf_hi(uint32_t v) { return __uint_as_float(v & 0xffff0000u); }
__device__ __forceinline__ float rbf(float x) { return __bfloat162float(__float2bfloat16_rn(x)); }

__device__ __forceinline__ uint32_t desc_lo(uint32_t addr) { return ((addr & 0x3FFFF) >> 4) | ((uint32_t)(HALF >> 4) << 16); }
__device__ __forceinline__ uint64_t desc(uint32_t lo) { return (uint64_t)lo | ((uint64_t)(64u | (1u << 30)) << 32); }

template<int TB> __device__ __forceinline__ void wgmma_ss_n128(float (&d)[64], uint64_t descA, uint64_t descB, int scaleD) {
  asm volatile("{\n.reg .pred p;\nsetp.ne.b32 p, %66, 0;\n"
    "wgmma.mma_async.sync.aligned.m64n128k16.f32.bf16.bf16 "
    "{%0, %1, %2, %3, %4, %5, %6, %7, %8, %9, %10, %11, %12, %13, %14, %15, "
    "%16, %17, %18, %19, %20, %21, %22, %23, %24, %25, %26, %27, %28, %29, %30, %31, "
    "%32, %33, %34, %35, %36, %37, %38, %39, %40, %41, %42, %43, %44, %45, %46, %47, "
    "%48, %49, %50, %51, %52, %53, %54, %55, %56, %57, %58, %59, %60, %61, %62, %63}, "
    "%64, %65, p, 1, 1, 0, %67;\n}\n"
    : "+f"(d[0]), "+f"(d[1]), "+f"(d[2]), "+f"(d[3]), "+f"(d[4]), "+f"(d[5]), "+f"(d[6]), "+f"(d[7]),
      "+f"(d[8]), "+f"(d[9]), "+f"(d[10]), "+f"(d[11]), "+f"(d[12]), "+f"(d[13]), "+f"(d[14]), "+f"(d[15]),
      "+f"(d[16]), "+f"(d[17]), "+f"(d[18]), "+f"(d[19]), "+f"(d[20]), "+f"(d[21]), "+f"(d[22]), "+f"(d[23]),
      "+f"(d[24]), "+f"(d[25]), "+f"(d[26]), "+f"(d[27]), "+f"(d[28]), "+f"(d[29]), "+f"(d[30]), "+f"(d[31]),
      "+f"(d[32]), "+f"(d[33]), "+f"(d[34]), "+f"(d[35]), "+f"(d[36]), "+f"(d[37]), "+f"(d[38]), "+f"(d[39]),
      "+f"(d[40]), "+f"(d[41]), "+f"(d[42]), "+f"(d[43]), "+f"(d[44]), "+f"(d[45]), "+f"(d[46]), "+f"(d[47]),
      "+f"(d[48]), "+f"(d[49]), "+f"(d[50]), "+f"(d[51]), "+f"(d[52]), "+f"(d[53]), "+f"(d[54]), "+f"(d[55]),
      "+f"(d[56]), "+f"(d[57]), "+f"(d[58]), "+f"(d[59]), "+f"(d[60]), "+f"(d[61]), "+f"(d[62]), "+f"(d[63])
    : "l"(descA), "l"(descB), "r"(scaleD), "n"(TB));
}

template<int TB> __device__ __forceinline__ void wgmma_rs_n128(float (&d)[64], uint32_t a0, uint32_t a1, uint32_t a2, uint32_t a3, uint64_t descB, int scaleD) {
  asm volatile("{\n.reg .pred p;\nsetp.ne.b32 p, %69, 0;\n"
    "wgmma.mma_async.sync.aligned.m64n128k16.f32.bf16.bf16 "
    "{%0, %1, %2, %3, %4, %5, %6, %7, %8, %9, %10, %11, %12, %13, %14, %15, "
    "%16, %17, %18, %19, %20, %21, %22, %23, %24, %25, %26, %27, %28, %29, %30, %31, "
    "%32, %33, %34, %35, %36, %37, %38, %39, %40, %41, %42, %43, %44, %45, %46, %47, "
    "%48, %49, %50, %51, %52, %53, %54, %55, %56, %57, %58, %59, %60, %61, %62, %63}, "
    "{%64, %65, %66, %67}, %68, p, 1, 1, %70;\n}\n"
    : "+f"(d[0]), "+f"(d[1]), "+f"(d[2]), "+f"(d[3]), "+f"(d[4]), "+f"(d[5]), "+f"(d[6]), "+f"(d[7]),
      "+f"(d[8]), "+f"(d[9]), "+f"(d[10]), "+f"(d[11]), "+f"(d[12]), "+f"(d[13]), "+f"(d[14]), "+f"(d[15]),
      "+f"(d[16]), "+f"(d[17]), "+f"(d[18]), "+f"(d[19]), "+f"(d[20]), "+f"(d[21]), "+f"(d[22]), "+f"(d[23]),
      "+f"(d[24]), "+f"(d[25]), "+f"(d[26]), "+f"(d[27]), "+f"(d[28]), "+f"(d[29]), "+f"(d[30]), "+f"(d[31]),
      "+f"(d[32]), "+f"(d[33]), "+f"(d[34]), "+f"(d[35]), "+f"(d[36]), "+f"(d[37]), "+f"(d[38]), "+f"(d[39]),
      "+f"(d[40]), "+f"(d[41]), "+f"(d[42]), "+f"(d[43]), "+f"(d[44]), "+f"(d[45]), "+f"(d[46]), "+f"(d[47]),
      "+f"(d[48]), "+f"(d[49]), "+f"(d[50]), "+f"(d[51]), "+f"(d[52]), "+f"(d[53]), "+f"(d[54]), "+f"(d[55]),
      "+f"(d[56]), "+f"(d[57]), "+f"(d[58]), "+f"(d[59]), "+f"(d[60]), "+f"(d[61]), "+f"(d[62]), "+f"(d[63])
    : "r"(a0), "r"(a1), "r"(a2), "r"(a3), "l"(descB), "r"(scaleD), "n"(TB));
}

template<int TB> __device__ __forceinline__ void wgmma_rs_n64(float (&d)[64], uint32_t a0, uint32_t a1, uint32_t a2, uint32_t a3, uint64_t descB, int scaleD) {
  asm volatile("{\n.reg .pred p;\nsetp.ne.b32 p, %37, 0;\n"
    "wgmma.mma_async.sync.aligned.m64n64k16.f32.bf16.bf16 "
    "{%0, %1, %2, %3, %4, %5, %6, %7, %8, %9, %10, %11, %12, %13, %14, %15, "
    "%16, %17, %18, %19, %20, %21, %22, %23, %24, %25, %26, %27, %28, %29, %30, %31}, "
    "{%32, %33, %34, %35}, %36, p, 1, 1, %38;\n}\n"
    : "+f"(d[0]), "+f"(d[1]), "+f"(d[2]), "+f"(d[3]), "+f"(d[4]), "+f"(d[5]), "+f"(d[6]), "+f"(d[7]),
      "+f"(d[8]), "+f"(d[9]), "+f"(d[10]), "+f"(d[11]), "+f"(d[12]), "+f"(d[13]), "+f"(d[14]), "+f"(d[15]),
      "+f"(d[16]), "+f"(d[17]), "+f"(d[18]), "+f"(d[19]), "+f"(d[20]), "+f"(d[21]), "+f"(d[22]), "+f"(d[23]),
      "+f"(d[24]), "+f"(d[25]), "+f"(d[26]), "+f"(d[27]), "+f"(d[28]), "+f"(d[29]), "+f"(d[30]), "+f"(d[31])
    : "r"(a0), "r"(a1), "r"(a2), "r"(a3), "l"(descB), "r"(scaleD), "n"(TB));
}

struct Cur {
  uint32_t o, phase;
  __device__ __forceinline__ void adv() { o += 8; if (o == 8 * NSLOT) { o = 0; phase ^= 1; } }
};

struct Params {
  CUtensorMap ckv, xn, x, wq, wuk, wuv, wo, out;
  const __nv_bfloat16 *px, *w_r, *w_gate, *w_up, *w_down;
  float neg;
  uint32_t zero;
};

__device__ __forceinline__ void moe_cta(const Params& P, int q, unsigned ep, uint8_t* smem) {
  float* xs = (float*)smem;
  float* red = xs + DM;
  float* hs = red + 2 * 8 * 344;
  float* sv = hs + 344; int* si = (int*)(sv + 16);
  const int tid = threadIdx.x, lane = tid & 31, warp = tid >> 5;
  if (tid < 16) flag_wait(F_LN + tid, ep * 8);
  __syncthreads();
  float bv = -INFINITY; int bi = 0x7fffffff;
  for (int i = tid; i < SEQ; i += 384) { float v = __ldcg(&g_r[i]); if (v > bv || bi == 0x7fffffff) { bv = v; bi = i; } }
#pragma unroll
  for (int o = 16; o; o >>= 1) {
    float ov = __shfl_xor_sync(~0u, bv, o); int oi = __shfl_xor_sync(~0u, bi, o);
    if (ov > bv || (ov == bv && oi < bi)) { bv = ov; bi = oi; }
  }
  if (lane == 0) { sv[warp] = bv; si[warp] = bi; }
  __syncthreads();
  bv = sv[0]; bi = si[0];
  for (int w = 1; w < 12; w++) { float ov = sv[w]; int oi = si[w]; if (ov > bv || (ov == bv && oi < bi)) { bv = ov; bi = oi; } }
  for (int i = tid; i < DM; i += 384) xs[i] = __bfloat162float(__ldcg(&g_xn[bi * DM + i]));
  __syncthreads();
  const int f0 = q * 344;
  if (tid < 344) {
    const int cg = tid % 43, ksl = tid / 43;
    float ag[8], au[8];
#pragma unroll
    for (int i = 0; i < 8; i++) ag[i] = au[i] = 0.f;
    const __nv_bfloat16* pg = P.w_gate + (size_t)(ksl * 64) * FF + f0 + cg * 8;
    const __nv_bfloat16* pu = P.w_up + (size_t)(ksl * 64) * FF + f0 + cg * 8;
#pragma unroll 8
    for (int k = 0; k < 64; k++) {
      uint4 a = __ldg((const uint4*)(pg + (size_t)k * FF)), b = __ldg((const uint4*)(pu + (size_t)k * FF));
      float xv = xs[ksl * 64 + k];
      ag[0] += xv * bf_lo(a.x); ag[1] += xv * bf_hi(a.x); ag[2] += xv * bf_lo(a.y); ag[3] += xv * bf_hi(a.y);
      ag[4] += xv * bf_lo(a.z); ag[5] += xv * bf_hi(a.z); ag[6] += xv * bf_lo(a.w); ag[7] += xv * bf_hi(a.w);
      au[0] += xv * bf_lo(b.x); au[1] += xv * bf_hi(b.x); au[2] += xv * bf_lo(b.y); au[3] += xv * bf_hi(b.y);
      au[4] += xv * bf_lo(b.z); au[5] += xv * bf_hi(b.z); au[6] += xv * bf_lo(b.w); au[7] += xv * bf_hi(b.w);
    }
#pragma unroll
    for (int i = 0; i < 8; i++) { red[ksl * 344 + cg * 8 + i] = ag[i]; red[(8 + ksl) * 344 + cg * 8 + i] = au[i]; }
  }
  __syncthreads();
  if (tid < 344) {
    float g = 0.f, u = 0.f;
#pragma unroll
    for (int i = 0; i < 8; i++) { g += red[i * 344 + tid]; u += red[(8 + i) * 344 + tid]; }
    g = rbf(g); u = rbf(u);
    g = rbf(g / (1.f + expf(-g)));
    hs[tid] = rbf(g * u);
  }
  __syncthreads();
  {
    const int cg = tid & 63, fs = tid >> 6;
    float ay[8];
#pragma unroll
    for (int i = 0; i < 8; i++) ay[i] = 0.f;
    const __nv_bfloat16* pd = P.w_down + (size_t)f0 * DM + cg * 8;
#pragma unroll 8
    for (int f = fs; f < 344; f += 6) {
      uint4 a = __ldg((const uint4*)(pd + (size_t)f * DM));
      float hv = hs[f];
      ay[0] += hv * bf_lo(a.x); ay[1] += hv * bf_hi(a.x); ay[2] += hv * bf_lo(a.y); ay[3] += hv * bf_hi(a.y);
      ay[4] += hv * bf_lo(a.z); ay[5] += hv * bf_hi(a.z); ay[6] += hv * bf_lo(a.w); ay[7] += hv * bf_hi(a.w);
    }
#pragma unroll
    for (int i = 0; i < 8; i++) red[fs * DM + cg * 8 + i] = ay[i];
  }
  __syncthreads();
  for (int i = tid; i < DM; i += 384) {
    float y = 0.f;
#pragma unroll
    for (int s = 0; s < 6; s++) y += red[s * DM + i];
    g_ypart[q * DM + i] = y;
  }
  if (q == 0 && tid == 0) { g_sel = bi; g_gate = rbf(1.f / (1.f + expf(-bv))); }
  __syncthreads();
  if (tid == 0) { __threadfence(); flag_add(F_MOE); }
}

__device__ __forceinline__ float half_sum(float v) {
#pragma unroll
  for (int o = 8; o; o >>= 1) v += __shfl_xor_sync(~0u, v, o);
  return v;
}
__device__ __forceinline__ void ln_row(const Params& P, int row, int l16, const uint4 (&xi)[4], const uint4 (&wi)[4]) {
  uint32_t x[16], w[16];
#pragma unroll
  for (int i = 0; i < 4; i++) {
    x[4 * i] = xi[i].x; x[4 * i + 1] = xi[i].y; x[4 * i + 2] = xi[i].z; x[4 * i + 3] = xi[i].w;
    w[4 * i] = wi[i].x; w[4 * i + 1] = wi[i].y; w[4 * i + 2] = wi[i].z; w[4 * i + 3] = wi[i].w;
  }
  float s[4] = {0.f, 0.f, 0.f, 0.f};
#pragma unroll
  for (int k = 0; k < 16; k++) { s[k & 1] += bf_lo(x[k]); s[2 + (k & 1)] += bf_hi(x[k]); }
  const float mean = half_sum((s[0] + s[1]) + (s[2] + s[3])) * (1.f / DM);
  s[0] = s[1] = s[2] = s[3] = 0.f;
#pragma unroll
  for (int k = 0; k < 16; k++) {
    const float d0 = bf_lo(x[k]) - mean, d1 = bf_hi(x[k]) - mean;
    s[k & 1] = fmaf(d0, d0, s[k & 1]); s[2 + (k & 1)] = fmaf(d1, d1, s[2 + (k & 1)]);
  }
  const float var = half_sum((s[0] + s[1]) + (s[2] + s[3])) * (1.f / DM);
  const uint32_t mb = pack_bf16(mean, mean);
  const float rs = __frcp_rn(rbf(__fsqrt_rn(rbf(rbf(var) + 1e-5f))));
  s[0] = s[1] = s[2] = s[3] = 0.f;
#pragma unroll
  for (int k = 0; k < 16; k++) {
    uint32_t d;
    asm("sub.rn.bf16x2 %0, %1, %2;" : "=r"(d) : "r"(x[k]), "r"(mb));
    x[k] = pack_bf16(bf_lo(d) * rs, bf_hi(d) * rs);
    s[k & 1] = fmaf(bf_lo(x[k]), bf_lo(w[k]), s[k & 1]); s[2 + (k & 1)] = fmaf(bf_hi(x[k]), bf_hi(w[k]), s[2 + (k & 1)]);
  }
  uint4* dst = (uint4*)(g_xn + (size_t)row * DM) + l16;
#pragma unroll
  for (int i = 0; i < 4; i++) dst[16 * i] = make_uint4(x[4 * i], x[4 * i + 1], x[4 * i + 2], x[4 * i + 3]);
  const float r = half_sum((s[0] + s[1]) + (s[2] + s[3]));
  if (l16 == 0) g_r[row] = rbf(r);
}

struct Ctx {
  uint32_t sb;
  uint32_t dlo;
  uint32_t full0;
  uint32_t rel;
  bool rel_pred, warp0;
  uint32_t stg;
  uint32_t stg_full, stg_empty;
  uint32_t stg_phase;
  uint32_t frag_off;
  uint32_t frag_x;
  int w;
  float neg;
  uint32_t zero;
  __device__ __forceinline__ void wait(const Cur& c) const { mbar_wait(full0 + c.o, c.phase); }
  __device__ __forceinline__ void release(const Cur& c) const { mbar_arrive_cluster_if(rel + c.o, rel_pred); }
  __device__ __forceinline__ void skip(const Cur& c) const { if (warp0) { wait(c); release(c); } }
  __device__ __forceinline__ uint32_t addr(const Cur& c) const { return sb + c.o * (TILE / 8); }
  __device__ __forceinline__ uint32_t dsc(const Cur& c) const { return dlo + c.o * (TILE / 128); }
  __device__ __forceinline__ void turn_begin() const { bar_sync(1 + w, 256); }
  __device__ __forceinline__ void turn_end() const { bar_arrive(2 - w, 256); }
  __device__ __forceinline__ uint32_t frag(int jj, int hstride) const { return (jj >> 2) * hstride + frag_off + (((jj & 3) * 32) ^ frag_x); }
  template <bool SCALE> __device__ __forceinline__ void stage_out(const float (&d)[64], float s0, float s1) {
    mbar_wait(stg_empty, stg_phase ^ 1);
    stg_phase ^= 1;
#pragma unroll
    for (int jj = 0; jj < 8; jj++) {
      if (SCALE)
        stsm4(stg + frag(jj, 8192), pack_bf16(d[8 * jj] * s0, d[8 * jj + 1] * s0), pack_bf16(d[8 * jj + 2] * s1, d[8 * jj + 3] * s1),
              pack_bf16(d[8 * jj + 4] * s0, d[8 * jj + 5] * s0), pack_bf16(d[8 * jj + 6] * s1, d[8 * jj + 7] * s1));
      else
        stsm4(stg + frag(jj, 8192), pack_bf16(d[8 * jj], d[8 * jj + 1]), pack_bf16(d[8 * jj + 2], d[8 * jj + 3]),
              pack_bf16(d[8 * jj + 4], d[8 * jj + 5]), pack_bf16(d[8 * jj + 6], d[8 * jj + 7]));
    }
  }
  __device__ __forceinline__ void publish() const { fence_async_smem(); mbar_arrive(stg_full); }
};

constexpr float SM_SCALE = 0.08838834764831845f * 1.4426950408889634f;
constexpr float SUM_LIMIT = 1152921504606846976.f;

struct Attn {
  float o[64], s[64];
  uint32_t p[32], q[32];
  float n0, n1;
  float l0, l1;
};

__device__ __forceinline__ void issue_qk(Attn& A, uint32_t d) {
#pragma unroll
  for (int kk = 0; kk < 8; kk++)
    wgmma_rs_n128<0>(A.s, A.q[4 * kk], A.q[4 * kk + 1], A.q[4 * kk + 2], A.q[4 * kk + 3], desc(d + (((kk >> 2) * HALF + (kk & 3) * 32) >> 4)), kk > 0);
  wg_commit();
}
__device__ __forceinline__ void issue_pv(Attn& A, uint32_t d, int acc) {
#pragma unroll
  for (int kk = 0; kk < 8; kk++)
    wgmma_rs_n128<1>(A.o, A.p[4 * kk], A.p[4 * kk + 1], A.p[4 * kk + 2], A.p[4 * kk + 3], desc(d + ((kk * 2048) >> 4)), kk > 0 ? 1 : acc);
  wg_commit();
}
__device__ __forceinline__ void pack_p(Attn& A) {
#pragma unroll
  for (int i = 0; i < 32; i++) A.p[i] = pack_bf16(A.s[2 * i], A.s[2 * i + 1]);
}
__device__ __forceinline__ void block_max(const Attn& A, float& n0, float& n1) {
  float x0 = fmaxf(A.s[0], A.s[1]), x1 = fmaxf(A.s[2], A.s[3]);
  float y0 = fmaxf(A.s[4], A.s[5]), y1 = fmaxf(A.s[6], A.s[7]);
#pragma unroll
  for (int j = 2; j < 16; j += 2) {
    x0 = fmaxf(x0, fmaxf(A.s[4 * j], A.s[4 * j + 1])); x1 = fmaxf(x1, fmaxf(A.s[4 * j + 2], A.s[4 * j + 3]));
    y0 = fmaxf(y0, fmaxf(A.s[4 * j + 4], A.s[4 * j + 5])); y1 = fmaxf(y1, fmaxf(A.s[4 * j + 6], A.s[4 * j + 7]));
  }
  x0 = fmaxf(x0, y0); x1 = fmaxf(x1, y1);
  x0 = fmaxf(x0, __shfl_xor_sync(~0u, x0, 1)); x1 = fmaxf(x1, __shfl_xor_sync(~0u, x1, 1));
  x0 = fmaxf(x0, __shfl_xor_sync(~0u, x0, 2)); x1 = fmaxf(x1, __shfl_xor_sync(~0u, x1, 2));
  n0 = -x0 * SM_SCALE; n1 = -x1 * SM_SCALE;
}
template <int J0, int J1> __device__ __forceinline__ void exp_cols(Attn& A, float (&a)[4]) {
#pragma unroll
  for (int j = J0; j < J1; j++) {
    A.s[4 * j] = ex2(fmaf(A.s[4 * j], SM_SCALE, A.n0)); A.s[4 * j + 1] = ex2(fmaf(A.s[4 * j + 1], SM_SCALE, A.n0));
    A.s[4 * j + 2] = ex2(fmaf(A.s[4 * j + 2], SM_SCALE, A.n1)); A.s[4 * j + 3] = ex2(fmaf(A.s[4 * j + 3], SM_SCALE, A.n1));
    if (j == 0) { a[0] = A.s[0]; a[1] = A.s[1]; a[2] = A.s[2]; a[3] = A.s[3]; }
    else { a[0] += A.s[4 * j]; a[1] += A.s[4 * j + 1]; a[2] += A.s[4 * j + 2]; a[3] += A.s[4 * j + 3]; }
  }
}
__device__ __forceinline__ void pin(float v, float neg, uint32_t addr) {
  asm volatile("{\n.reg .pred p;\nsetp.lt.f32 p, %0, %2;\n@p mbarrier.arrive.shared::cta.b64 _, [%1];\n}" :: "f"(v), "r"(addr), "f"(neg) : "memory");
}
__device__ __forceinline__ void causal_mask(Attn& A, int rel) {
#pragma unroll
  for (int j = 0; j < 16; j++) {
    if (8 * j > rel) A.s[4 * j] = -INFINITY;
    if (8 * j + 1 > rel) A.s[4 * j + 1] = -INFINITY;
    if (8 * j > rel + 8) A.s[4 * j + 2] = -INFINITY;
    if (8 * j + 1 > rel + 8) A.s[4 * j + 3] = -INFINITY;
  }
}
__device__ __forceinline__ void finish_item(Ctx& C, Attn& A, float l0, float l1) {
  l0 += __shfl_xor_sync(~0u, l0, 1); l1 += __shfl_xor_sync(~0u, l1, 1);
  l0 += __shfl_xor_sync(~0u, l0, 2); l1 += __shfl_xor_sync(~0u, l1, 2);
  C.stage_out<true>(A.o, __fdividef(1.f, l0), __fdividef(1.f, l1));
}
__device__ __forceinline__ void redo_block(Attn& A, const uint8_t* ktile, bool diag, int rel, uint32_t zero) {
  const int lane = threadIdx.x & 31;
  uint32_t off = (lane >> 2) * 144 + (lane & 3) * 4;
#pragma unroll
  for (int j = 0; j < 16; j++) {
    float c0 = 0.f, c1 = 0.f, c2 = 0.f, c3 = 0.f;
    if (j > 0) off += __float_as_uint(A.s[4 * j - 4]) & zero;
#pragma unroll
    for (int kk = 0; kk < 8; kk++) {
      const uint32_t b0 = __ldcg((const uint32_t*)(ktile + (off ^ ((kk & 3) * 32)) + j * 1024 + (kk >> 2) * HALF));
      const uint32_t b1 = __ldcg((const uint32_t*)(ktile + (off ^ ((kk & 3) * 32 + 16)) + j * 1024 + (kk >> 2) * HALF));
      asm volatile("mma.sync.aligned.m16n8k16.row.col.f32.bf16.bf16.f32 {%0, %1, %2, %3}, {%4, %5, %6, %7}, {%8, %9}, {%0, %1, %2, %3};"
                   : "+f"(c0), "+f"(c1), "+f"(c2), "+f"(c3)
                   : "r"(A.q[4 * kk]), "r"(A.q[4 * kk + 1]), "r"(A.q[4 * kk + 2]), "r"(A.q[4 * kk + 3]), "r"(b0), "r"(b1) : "memory");
    }
    A.s[4 * j] = c0; A.s[4 * j + 1] = c1; A.s[4 * j + 2] = c2; A.s[4 * j + 3] = c3;
  }
  if (diag) causal_mask(A, rel);
  float n0, n1, a[4];
  block_max(A, n0, n1);
  n0 = fminf(n0, A.n0); n1 = fminf(n1, A.n1);
  const float c0 = ex2(n0 - A.n0), c1 = ex2(n1 - A.n1);
  A.n0 = n0; A.n1 = n1;
  exp_cols<0, 16>(A, a);
  A.l0 = fmaf(A.l0, c0, a[0] + a[1]); A.l1 = fmaf(A.l1, c1, a[2] + a[3]);
#pragma unroll
  for (int j = 0; j < 16; j++) { A.o[4 * j] *= c0; A.o[4 * j + 1] *= c0; A.o[4 * j + 2] *= c1; A.o[4 * j + 3] *= c1; }
  pack_p(A);
}
template <bool HAS_PREV> __device__ __forceinline__ void item_begin(Ctx& C, Attn& A, Cur& cur, bool skip, int pv_acc, bool pub, bool diag, int rel) {
  Cur cq, ck, cv, cs;
  if (HAS_PREV && skip) { C.skip(cur); cur.adv(); cv = cur; cur.adv(); }
  cq = cur; cur.adv();
  ck = cur; cur.adv();
  if (HAS_PREV) { cs = cur; cur.adv(); if (!skip) cv = cs; }
  C.wait(cq);
  {
    const uint32_t qa = C.addr(cq) + C.w * 8192;
#pragma unroll
    for (int jj = 0; jj < 8; jj++) ldsm4(qa + C.frag(jj, HALF), A.q[4 * jj], A.q[4 * jj + 1], A.q[4 * jj + 2], A.q[4 * jj + 3]);
  }
  C.wait(ck);
  C.turn_begin();
  wg_fence();
  issue_qk(A, C.dsc(ck));
  if (HAS_PREV) { C.wait(cv); wg_fence(); issue_pv(A, C.dsc(cv), pv_acc); }
  C.turn_end();
  if (pub) C.publish();
  if (HAS_PREV) wg_wait<1>(); else wg_wait<0>();
  reg_fence(A.s);
  C.release(cq); C.release(ck);
  if (diag) causal_mask(A, rel);
  block_max(A, A.n0, A.n1);
  if (HAS_PREV) {
    wg_wait<0>();
    reg_fence(A.o);
    C.release(cv);
    finish_item(C, A, A.l0, A.l1);
  }
  float a[4];
  exp_cols<0, 16>(A, a);
  A.l0 = a[0] + a[1]; A.l1 = a[2] + a[3];
  pack_p(A);
  if (HAS_PREV && skip) C.skip(cs);
}
__device__ __forceinline__ void item_step(Ctx& C, Attn& A, Cur& cur, int pv_acc, bool pub, bool diag, int rel, const uint8_t* ktile) {
  const Cur ck = cur; cur.adv();
  const Cur cv = cur; cur.adv();
  C.wait(ck);
  C.turn_begin();
  wg_fence();
  issue_qk(A, C.dsc(ck));
  C.wait(cv);
  wg_fence();
  issue_pv(A, C.dsc(cv), pv_acc);
  C.turn_end();
  if (pub) C.publish();
  wg_wait<1>();
  reg_fence(A.s);
  C.release(ck);
  if (diag) causal_mask(A, rel);
  float a[4];
  exp_cols<0, 8>(A, a);
  pin((a[0] + a[1]) + (a[2] + a[3]), C.neg, C.stg_full);
  wg_wait<0>();
  reg_fence(A.o);
  C.release(cv);
  exp_cols<8, 16>(A, a);
  pack_p(A);
  const float b0 = a[0] + a[1], b1 = a[2] + a[3];
  if (__builtin_expect(__any_sync(~0u, !(b0 + b1 <= SUM_LIMIT)), 0)) redo_block(A, ktile, diag, rel, C.zero);
  else { A.l0 += b0; A.l1 += b1; }
}

template <bool LOAD_A> __device__ __forceinline__ void proj_unit(Ctx& C, Cur& cur, uint32_t (&a)[128], float (&acc)[64], bool pub) {
#pragma unroll
  for (int i = 0; i < 4; i++) {
    Cur ca = cur;
    if (LOAD_A) {
      cur.adv();
      C.wait(ca);
      const uint32_t aa = C.addr(ca) + C.w * 8192;
#pragma unroll
      for (int jj = 0; jj < 8; jj++) ldsm4(aa + C.frag(jj, HALF), a[32 * i + 4 * jj], a[32 * i + 4 * jj + 1], a[32 * i + 4 * jj + 2], a[32 * i + 4 * jj + 3]);
    }
    const Cur cb = cur; cur.adv();
    C.wait(cb);
    C.turn_begin();
    wg_fence();
    const uint32_t d = C.dsc(cb);
#pragma unroll
    for (int kk = 0; kk < 8; kk++)
      wgmma_rs_n128<1>(acc, a[32 * i + 4 * kk], a[32 * i + 4 * kk + 1], a[32 * i + 4 * kk + 2], a[32 * i + 4 * kk + 3], desc(d + ((kk * 2048) >> 4)), (i | kk) > 0);
    wg_commit();
    C.turn_end();
    if (i == 0 && pub) C.publish();
    wg_wait<0>();
    reg_fence(acc);
    if (LOAD_A) C.release(ca);
    C.release(cb);
  }
  C.stage_out<false>(acc, 1.f, 1.f);
}

__global__ void __cluster_dims__(2, 1, 1) __launch_bounds__(384, 1) fused_kernel(const __grid_constant__ Params P) {
  extern __shared__ uint8_t smem_raw[];
  uint8_t* smem = smem_raw + ((1024 - (smem_u32(smem_raw) & 1023)) & 1023);
  const int tid = threadIdx.x;
  const int c = blockIdx.x >> 1, r = blockIdx.x & 1;
  const unsigned ep = g_epoch[blockIdx.x] + 1;
  if (c >= 64) {
    moe_cta(P, blockIdx.x - 128, ep, smem);
    if (tid == 0) g_epoch[blockIdx.x] = ep;
    return;
  }
  const int rp = c & 7, g = c >> 3;
  const int rb = 2 * rp + r;
  const int ln_r = rb * 128 + 16 * g + ((tid >> 4) & 15);
  uint4 ln_x[4], ln_w[4];
#pragma unroll
  for (int i = 0; i < 4; i++) {
    ln_x[i] = __ldg((const uint4*)(P.px + (size_t)ln_r * DM) + 16 * i + (tid & 15));
    ln_w[i] = __ldg((const uint4*)P.w_r + 16 * i + (tid & 15));
  }
  const uint32_t sb = smem_u32(smem);
  const uint32_t full0 = sb + SMEM_BAR, empty0 = full0 + 8 * NSLOT, stgf0 = empty0 + 8 * NSLOT, stge0 = stgf0 + 16;
  if (tid == 0) {
    for (int i = 0; i < NSLOT; i++) { mbar_init(full0 + 8 * i, 1); mbar_init(empty0 + 8 * i, 4); }
    for (int i = 0; i < 2; i++) { mbar_init(stgf0 + 8 * i, 128); mbar_init(stge0 + 8 * i, 1); }
    asm volatile("fence.mbarrier_init.release.cluster;" ::: "memory");
  }
  asm volatile("barrier.cluster.arrive.aligned;\nbarrier.cluster.wait.aligned;" ::: "memory");

  const int ma = rp & 3, hb = rp >> 2;
  const int j3 = c & 15, ks = c >> 5, ncol = 2 * ((c >> 4) & 1) + r;
  const int wg = __shfl_sync(~0u, tid >> 7, 0);

  if (wg == 0) {
    asm volatile("setmaxnreg.dec.sync.aligned.u32 40;");
    const int warp = tid >> 5;
    if (warp == 0) {
      if (tid == 0) {
        Cur cur{0, 0};
        uint32_t dst, bar;
        auto acquire = [&]() {
          mbar_wait(empty0 + cur.o, cur.phase ^ 1);
          dst = sb + cur.o * (TILE / 8); bar = full0 + cur.o;
          mbar_expect(bar, TILE);
          cur.adv();
        };
        for (int u = 0; u < 12; u++) {
          const CUtensorMap* wm = u >= 8 ? &P.wq : ((u & 1) ? &P.wuv : &P.wuk);
          const CUtensorMap* am = u >= 8 ? &P.xn : &P.ckv;
          const int head = 4 * g + (u >= 8 ? u - 8 : u >> 1);
          if (u == 8) { flag_wait(F_LN + rb, ep * 8); fence_async_all(); }
          for (int i = 0; i < 4; i++) {
            if ((u & 7) == 0) {
              acquire();
              tma_load(dst, am, 128 * i, rb * 128, bar);
              tma_load(dst + HALF, am, 128 * i + 64, rb * 128, bar);
            }
            acquire();
            tma_load_mc(dst + r * HALF, wm, head * 128 + 64 * r, 128 * i, bar);
          }
        }
        const uint8_t* prev_v = nullptr;
        for (int it = 0; it < 4; it++) {
          const int head = 4 * g + (it & 2) + hb;
          const int m = (it & 1) ? ma : 7 - ma;
          const int j = 2 * m + (r ^ (it & 1));
          if (!(it & 1)) { flag_wait(F_HEAD + head, ep * 32); fence_async_all(); }
          acquire();
          bulk_load(dst, g_qkv + (size_t)(head * 16 + j) * TILE, TILE, bar);
          for (int b = 0; b <= 2 * m + 1; b++) {
            acquire();
            bulk_load_mc(dst + r * HALF, g_qkv + (size_t)((NH + head) * 16 + b) * TILE + r * HALF, HALF, bar);
            if (prev_v) { acquire(); bulk_load_mc(dst + r * HALF, prev_v, HALF, bar); }
            prev_v = g_qkv + (size_t)((2 * NH + head) * 16 + b) * TILE + r * HALF;
          }
        }
        acquire(); bulk_load_mc(dst + r * HALF, prev_v, HALF, bar);
        for (int t = 0; t < 16; t++) {
          const int head = 16 * ks + 4 * ((t & 7) >> 1) + 2 * (t >> 3) + (t & 1);
          acquire();
          tma_load(dst + ks * HALF, &P.wo, ncol * 128, head * 128, bar);
          tma_load(dst + (ks ^ 1) * HALF, &P.wo, ncol * 128 + 64, head * 128, bar);
          if ((t & 7) == 0) { flag_wait(F_CTX + j3 * 4 + ks * 2 + (t >> 3), ep * 16); fence_async_all(); }
          acquire();
          bulk_load_mc(dst + r * HALF, g_ctx + (size_t)(head * 16 + j3) * TILE + r * HALF, HALF, bar);
        }
        flag_wait(F_LN + j3, ep * 8);
        flag_wait(F_MOE, ep * 4);
        fence_async_all();
        acquire();
        tma_load(dst, &P.x, ncol * 128 + 64 * ks, j3 * 128, bar);
        tma_load(dst + HALF, &P.xn, ncol * 128 + 64 * ks, j3 * 128, bar);
        for (int i = 0; i < NSLOT; i++) { mbar_wait(empty0 + cur.o, cur.phase ^ 1); cur.adv(); }
        g_epoch[blockIdx.x] = ep;
      }
    } else if (warp == 3) {
      bar_sync(3, 288);
      if (tid == 96) { __threadfence(); fence_async_all(); flag_add(F_LN + rb); }
    } else {
      if ((tid & 31) == 0) {
        const int w = warp - 1;
        const uint32_t stg = sb + SMEM_STG + w * HALF;
        for (int job = 0; job < 17; job++) {
          mbar_wait(stgf0 + 8 * w, job & 1);
          int flag = -1;
          if (job < 16) {
            uint8_t* d;
            if (job < 12) {
              const int head = 4 * g + (job >= 8 ? job - 8 : job >> 1);
              const int kind = job >= 8 ? 0 : 1 + (job & 1);
              d = g_qkv + (size_t)((kind * NH + head) * 16 + rb) * TILE;
              if (job >= 8) flag = F_HEAD + head;
            } else {
              const int it = job - 12;
              const int head = 4 * g + (it & 2) + hb;
              const int m = (it & 1) ? ma : 7 - ma;
              const int j = 2 * m + (r ^ (it & 1));
              d = g_ctx + (size_t)(head * 16 + j) * TILE;
              flag = F_CTX + j * 4 + (g >> 2) * 2 + (it >> 1);
            }
            bulk_store(d + w * 8192, stg, 8192);
            bulk_store(d + HALF + w * 8192, stg + 8192, 8192);
          } else {
            tma_store(&P.out, ncol * 128 + 64 * ks, j3 * 128 + 64 * w, stg);
          }
          asm volatile("cp.async.bulk.commit_group;" ::: "memory");
          asm volatile("cp.async.bulk.wait_group.read 0;" ::: "memory");
          mbar_arrive(stge0 + 8 * w);
          if (job >= 8) asm volatile("cp.async.bulk.wait_group 0;" ::: "memory");
          if (flag >= 0) { fence_async_all(); flag_add(flag); }
          if (w == 1 && job >= 8 && job < 12) TLX(28 + job - 8);
        }
      }
    }
  } else {
    asm volatile("setmaxnreg.inc.sync.aligned.u32 232;");
    const int t = tid & 127, lane = tid & 31, wi = t >> 5;
    Ctx C;
    C.neg = P.neg; C.zero = P.zero; C.sb = sb; C.dlo = desc_lo(sb); C.full0 = full0; C.w = wg - 1;
    asm("mapa.shared::cluster.u32 %0, %1, %2;" : "=r"(C.rel) : "r"(empty0), "r"(lane & 1));
    C.rel_pred = t < 2;
    C.warp0 = __shfl_sync(~0u, wi, 0) == 0;
    C.stg = sb + SMEM_STG + C.w * HALF;
    C.stg_full = stgf0 + 8 * C.w; C.stg_empty = stge0 + 8 * C.w; C.stg_phase = 0;
    C.frag_off = (16 * wi + (lane & 15)) * 128;
    C.frag_x = ((lane >> 4) ^ (lane & 7)) * 16;
    TL(C.w * 16 + 0);
    ln_row(P, ln_r, tid & 15, ln_x, ln_w);
    bar_arrive(3, 288);
    if (C.w == 1) bar_arrive(1, 256);
    Cur cur{0, 0};
    TL(C.w * 16 + 1);
    {
      uint32_t a[128];
      float acc[64];
#pragma unroll 1
      for (int half = 0; half < 2; half++) {
        proj_unit<true>(C, cur, a, acc, half);
        if (half == 0) TL(C.w * 16 + 2);
#pragma unroll 1
        for (int u = half ? 5 : 1; u < 8; u++) proj_unit<false>(C, cur, a, acc, true);
      }
    }
    TL(C.w * 16 + 3);
    {
      Attn A;
      const int rel = 64 * C.w + 16 * wi + (lane >> 2) - 2 * (lane & 3);
      A.l0 = A.l1 = 0.f;
      int pv_acc = 0;
      bool skip = false, pub = true;
#pragma unroll 1
      for (int it = 0; it < 4; it++) {
        const int m = (it & 1) ? ma : 7 - ma;
        const int role = r ^ (it & 1);
        const int j = 2 * m + role;
        if (it == 0) item_begin<false>(C, A, cur, false, 0, true, j == 0, rel);
        else item_begin<true>(C, A, cur, skip, pv_acc, pub, j == 0, rel);
        pv_acc = 0; pub = it > 0; skip = role == 0;
        const uint8_t* kt = g_qkv + (size_t)((NH + 4 * g + (it & 2) + hb) * 16) * TILE;
#pragma unroll 1
        for (int b = 1; b <= j; b++) { item_step(C, A, cur, pv_acc, pub, b == j, rel, kt + (size_t)b * TILE); pv_acc = 1; pub = false; }
        TL(C.w * 16 + 4 + it);
      }
      if (skip) { C.skip(cur); cur.adv(); }
      const Cur cv = cur; cur.adv();
      C.wait(cv);
      C.turn_begin();
      wg_fence();
      issue_pv(A, C.dsc(cv), pv_acc);
      C.turn_end();
      if (pub) C.publish();
      wg_wait<0>();
      reg_fence(A.o);
      C.release(cv);
      finish_item(C, A, A.l0, A.l1);
      C.publish();
      if (skip) { C.skip(cur); cur.adv(); }
      if (C.w == 0) C.turn_begin();
    }
    TL(C.w * 16 + 8);
    {
      float acc[64];
      Cur pb = cur, pa = cur;
#pragma unroll 1
      for (int h = 0; h < 16; h++) {
        const Cur cb = cur; cur.adv();
        const Cur ca = cur; cur.adv();
        C.wait(cb); C.wait(ca);
        wg_fence();
        const uint32_t da = C.dsc(ca) + C.w * 512, db = C.dsc(cb);
#pragma unroll
        for (int kk = 0; kk < 8; kk++)
          wgmma_ss_n128<1>(acc, desc(da + (((kk >> 2) * HALF + (kk & 3) * 32) >> 4)), desc(db + ((kk * 2048) >> 4)), kk > 0 ? 1 : h);
        wg_commit();
        wg_wait<1>();
        if (h > 0) { C.release(pb); C.release(pa); }
        pb = cb; pa = ca;
      }
      wg_wait<0>();
      reg_fence(acc);
      C.release(pb); C.release(pa);
      TL(C.w * 16 + 9);
      float4* mine = g_part + (size_t)blockIdx.x * 2048 + C.w * 1024 + t;
      const float4* theirs = g_part + (size_t)(blockIdx.x ^ 64) * 2048 + C.w * 1024 + t;
#pragma unroll
      for (int i = 0; i < 8; i++) __stcg(mine + i * 128, make_float4(acc[32 + 4 * i], acc[33 + 4 * i], acc[34 + 4 * i], acc[35 + 4 * i]));
      bar_sync(4 + C.w, 128);
      if (t == 0) {
        __threadfence();
        flag_add(F_PART + blockIdx.x * 2 + C.w);
        flag_wait(F_PART + (blockIdx.x ^ 64) * 2 + C.w, ep);
      }
      const Cur cr = cur;
      C.wait(cr);
      uint32_t xr[16], nr[16];
      const uint32_t xa = C.addr(cr) + C.w * 8192;
#pragma unroll
      for (int jj = 0; jj < 4; jj++) {
        ldsm4(xa + C.frag(jj, 0), xr[4 * jj], xr[4 * jj + 1], xr[4 * jj + 2], xr[4 * jj + 3]);
        ldsm4(xa + HALF + C.frag(jj, 0), nr[4 * jj], nr[4 * jj + 1], nr[4 * jj + 2], nr[4 * jj + 3]);
      }
      const int sel = __ldcg(&g_sel);
      const int row0 = j3 * 128 + 64 * C.w + 16 * wi + (lane >> 2);
      if (sel == row0 || sel == row0 + 8) {
        const float gate = __ldcg(&g_gate);
        const float* yp = g_ypart + ncol * 128 + 64 * ks + 2 * (lane & 3);
#pragma unroll
        for (int j = 0; j < 8; j++) {
          float y0 = 0.f, y1 = 0.f;
#pragma unroll
          for (int q = 0; q < 4; q++) { y0 += __ldcg(yp + q * DM + 8 * j); y1 += __ldcg(yp + q * DM + 8 * j + 1); }
          y0 = rbf(rbf(y0) * gate); y1 = rbf(rbf(y1) * gate);
          if (sel == row0) nr[2 * j] = pack_bf16(bf_lo(nr[2 * j]) + y0, bf_hi(nr[2 * j]) + y1);
          else nr[2 * j + 1] = pack_bf16(bf_lo(nr[2 * j + 1]) + y0, bf_hi(nr[2 * j + 1]) + y1);
        }
      }
      bar_sync(4 + C.w, 128);
      C.release(cr);
      TL(C.w * 16 + 10);
#pragma unroll
      for (int i = 0; i < 8; i++) {
        const float4 v = __ldcg(theirs + i * 128);
        acc[4 * i] += v.x; acc[4 * i + 1] += v.y; acc[4 * i + 2] += v.z; acc[4 * i + 3] += v.w;
      }
      uint32_t o[16];
#pragma unroll
      for (int i = 0; i < 16; i++)
        o[i] = pack_bf16(rbf(bf_lo(xr[i]) + rbf(acc[2 * i])) + bf_lo(nr[i]), rbf(bf_hi(xr[i]) + rbf(acc[2 * i + 1])) + bf_hi(nr[i]));
      mbar_wait(C.stg_empty, C.stg_phase ^ 1);
#pragma unroll
      for (int jj = 0; jj < 4; jj++) stsm4(C.stg + C.frag(jj, 0), o[4 * jj], o[4 * jj + 1], o[4 * jj + 2], o[4 * jj + 3]);
      fence_async_smem();
      mbar_arrive(C.stg_full);
      TL(C.w * 16 + 11);
    }
  }
}

typedef CUresult (*EncodeFn)(CUtensorMap*, CUtensorMapDataType, cuuint32_t, void*, const cuuint64_t*, const cuuint64_t*,
                             const cuuint32_t*, const cuuint32_t*, CUtensorMapInterleave, CUtensorMapSwizzle,
                             CUtensorMapL2promotion, CUtensorMapFloatOOBfill);

void make_map(EncodeFn fn, CUtensorMap* m, const void* ptr, uint64_t cols, uint64_t rows, uint32_t box_rows) {
  cuuint64_t dims[2] = {cols, rows};
  cuuint64_t strides[1] = {cols * 2};
  cuuint32_t box[2] = {64, box_rows};
  cuuint32_t es[2] = {1, 1};
  fn(m, CU_TENSOR_MAP_DATA_TYPE_BFLOAT16, 2, const_cast<void*>(ptr), dims, strides, box, es, CU_TENSOR_MAP_INTERLEAVE_NONE,
     CU_TENSOR_MAP_SWIZZLE_128B, CU_TENSOR_MAP_L2_PROMOTION_L2_128B, CU_TENSOR_MAP_FLOAT_OOB_FILL_NONE);
}

}

extern "C" void kernel_launch(void* const* d_in, const int* in_sizes, int n_in, void* d_out, int out_size) {
  static EncodeFn fn = nullptr;
  static void* xn_ptr = nullptr;
  if (!fn) {
    void* f = nullptr;
    cudaDriverEntryPointQueryResult qr;
    cudaGetDriverEntryPoint("cuTensorMapEncodeTiled", &f, cudaEnableDefault, &qr);
    fn = (EncodeFn)f;
    cudaGetSymbolAddress(&xn_ptr, g_xn);
    cudaFuncSetAttribute(fused_kernel, cudaFuncAttributeMaxDynamicSharedMemorySize, SMEM_TOTAL);
  }
  Params P;
  make_map(fn, &P.x, d_in[0], DM, SEQ, 128);
  make_map(fn, &P.ckv, d_in[1], DM, SEQ, 128);
  make_map(fn, &P.xn, xn_ptr, DM, SEQ, 128);
  make_map(fn, &P.wq, d_in[2], NH * 128, DM, 128);
  make_map(fn, &P.wuk, d_in[3], NH * 128, DM, 128);
  make_map(fn, &P.wuv, d_in[4], NH * 128, DM, 128);
  make_map(fn, &P.wo, d_in[5], DM, NH * 128, 128);
  make_map(fn, &P.out, d_out, DM, SEQ, 64);
  P.neg = -1.f;
  P.zero = 0;
  P.px = (const __nv_bfloat16*)d_in[0];
  P.w_r = (const __nv_bfloat16*)d_in[7];
  P.w_gate = (const __nv_bfloat16*)d_in[8];
  P.w_up = (const __nv_bfloat16*)d_in[9];
  P.w_down = (const __nv_bfloat16*)d_in[10];
  fused_kernel<<<NCTA, 384, SMEM_TOTAL>>>(P);
}
```

```cpp
#include <cuda_runtime.h>
#include <cuda_bf16.h>
#include <cuda.h>
#include <stdint.h>

namespace {

constexpr int SEQ = 2048, DM = 512, NH = 32, FF = 1376;
constexpr int NSLOT = 6;
constexpr int TILE = 32768;
constexpr int HALF = 16384;
constexpr int SMEM_STG = NSLOT * TILE;
constexpr int SMEM_BAR = SMEM_STG + 32768;
constexpr int SMEM_TOTAL = SMEM_BAR + 256 + 1024;
constexpr int NCTA = 132;
constexpr int SPIN_LIMIT = 1 << 22;

constexpr int F_LN = 0;
constexpr int F_GRP = 16;
constexpr int F_CTX = 40;
constexpr int F_MOE = 104;
constexpr int F_COUNT = 105;

__device__ __align__(1024) __nv_bfloat16 g_xn[SEQ * DM];
__device__ float g_r[SEQ];
__device__ __align__(1024) uint8_t g_qkv[3ull * NH * 16 * TILE];
__device__ __align__(1024) uint4 g_part[128 * 2 * 11 * 128];
__device__ float g_ypart[4 * DM];
__device__ int g_sel;
__device__ float g_gate;
__device__ unsigned g_flags[F_COUNT * 32];
__device__ unsigned g_epoch[NCTA];
#define TL(i)
#define TLX(i)

__device__ __forceinline__ uint32_t smem_u32(const void* p) { return (uint32_t)__cvta_generic_to_shared(p); }
__device__ __forceinline__ void mbar_init(uint32_t bar, int cnt) { asm volatile("mbarrier.init.shared::cta.b64 [%0], %1;" :: "r"(bar), "r"(cnt)); }
__device__ __forceinline__ void mbar_arrive(uint32_t bar) { asm volatile("mbarrier.arrive.shared::cta.b64 _, [%0];" :: "r"(bar) : "memory"); }
__device__ __forceinline__ void mbar_arrive_cluster_if(uint32_t bar, bool pred) {
  asm volatile("{\n.reg .pred p;\nsetp.ne.b32 p, %1, 0;\n@p mbarrier.arrive.shared::cluster.b64 _, [%0];\n}" :: "r"(bar), "r"((int)pred) : "memory");
}
__device__ __forceinline__ void mbar_expect(uint32_t bar, int bytes) { asm volatile("mbarrier.arrive.expect_tx.shared::cta.b64 _, [%0], %1;" :: "r"(bar), "r"(bytes) : "memory"); }
__device__ __forceinline__ void mbar_wait(uint32_t bar, uint32_t parity) {
  asm volatile("{\n.reg .pred p, q;\n.reg .b32 n;\n"
               "mbarrier.try_wait.parity.shared::cta.b64 p, [%0], %1;\n@p bra DONE;\nmov.b32 n, 0;\n"
               "LOOP:\nmbarrier.try_wait.parity.shared::cta.b64 p, [%0], %1;\nadd.s32 n, n, 1;\nsetp.lt.s32 q, n, %2;\n@p bra DONE;\n@q bra LOOP;\n"
               "DONE:\n}" :: "r"(bar), "r"(parity), "n"(SPIN_LIMIT) : "memory");
}
__device__ __forceinline__ void bulk_load(uint32_t dst, const void* src, int bytes, uint32_t bar) {
  asm volatile("cp.async.bulk.shared::cluster.global.mbarrier::complete_tx::bytes [%0], [%1], %2, [%3];" :: "r"(dst), "l"(src), "r"(bytes), "r"(bar) : "memory");
}
__device__ __forceinline__ void bulk_load_mc(uint32_t dst, const void* src, int bytes, uint32_t bar) {
  asm volatile("cp.async.bulk.shared::cluster.global.mbarrier::complete_tx::bytes.multicast::cluster [%0], [%1], %2, [%3], %4;" :: "r"(dst), "l"(src), "r"(bytes), "r"(bar), "h"((uint16_t)3) : "memory");
}
__device__ __forceinline__ void tma_load(uint32_t dst, const CUtensorMap* map, int c0, int c1, uint32_t bar) {
  asm volatile("cp.async.bulk.tensor.2d.shared::cluster.global.mbarrier::complete_tx::bytes [%0], [%1, {%3, %4}], [%2];" :: "r"(dst), "l"(map), "r"(bar), "r"(c0), "r"(c1) : "memory");
}
__device__ __forceinline__ void tma_load_mc(uint32_t dst, const CUtensorMap* map, int c0, int c1, uint32_t bar) {
  asm volatile("cp.async.bulk.tensor.2d.shared::cluster.global.mbarrier::complete_tx::bytes.multicast::cluster [%0], [%1, {%3, %4}], [%2], %5;" :: "r"(dst), "l"(map), "r"(bar), "r"(c0), "r"(c1), "h"((uint16_t)3) : "memory");
}
__device__ __forceinline__ void bulk_store(void* dst, uint32_t src, int bytes) {
  asm volatile("cp.async.bulk.global.shared::cta.bulk_group [%0], [%1], %2;" :: "l"(dst), "r"(src), "r"(bytes) : "memory");
}
__device__ __forceinline__ void st_tagged(uint4* p, float a, float b, float c, uint32_t tag) {
  asm volatile("{\n.reg .b128 v;\n.reg .b64 lo, hi;\nmov.b64 lo, {%1, %2};\nmov.b64 hi, {%3, %4};\nmov.b128 v, {lo, hi};\n"
               "st.relaxed.gpu.global.b128 [%0], v;\n}" :: "l"(p), "r"(__float_as_uint(a)), "r"(__float_as_uint(b)), "r"(__float_as_uint(c)), "r"(tag) : "memory");
}
__device__ __forceinline__ uint4 ld_tagged(const uint4* p) {
  uint4 r;
  asm volatile("{\n.reg .b128 v;\n.reg .b64 lo, hi;\nld.relaxed.gpu.global.b128 v, [%4];\nmov.b128 {lo, hi}, v;\n"
               "mov.b64 {%0, %1}, lo;\nmov.b64 {%2, %3}, hi;\n}" : "=r"(r.x), "=r"(r.y), "=r"(r.z), "=r"(r.w) : "l"(p) : "memory");
  return r;
}
__device__ __forceinline__ void fence_async_smem() { asm volatile("fence.proxy.async.shared::cta;" ::: "memory"); }
__device__ __forceinline__ void fence_async_all() { asm volatile("fence.proxy.async;" ::: "memory"); }
__device__ __forceinline__ void flag_add(int f) { asm volatile("red.release.gpu.global.add.u32 [%0], 1;" :: "l"(&g_flags[f * 32]) : "memory"); }
__device__ __forceinline__ void flag_wait(int f, unsigned target) {
  const unsigned* p = &g_flags[f * 32];
  for (int n = 0; n < SPIN_LIMIT; ++n) {
    unsigned v;
    asm volatile("ld.acquire.gpu.global.u32 %0, [%1];" : "=r"(v) : "l"(p) : "memory");
    if ((int)(v - target) >= 0) break;
  }
}
__device__ __forceinline__ void bar_sync(int id, int n) { asm volatile("bar.sync %0, %1;" :: "r"(id), "r"(n) : "memory"); }
__device__ __forceinline__ void bar_arrive(int id, int n) { asm volatile("bar.arrive %0, %1;" :: "r"(id), "r"(n) : "memory"); }
__device__ __forceinline__ void wg_fence() { asm volatile("wgmma.fence.sync.aligned;" ::: "memory"); }
__device__ __forceinline__ void wg_commit() { asm volatile("wgmma.commit_group.sync.aligned;" ::: "memory"); }
template <int N> __device__ __forceinline__ void wg_wait() { asm volatile("wgmma.wait_group.sync.aligned %0;" :: "n"(N) : "memory"); }
template <int N> __device__ __forceinline__ void reg_fence(float (&d)[N]) {
#pragma unroll
  for (int i = 0; i < N; i++) asm volatile("" : "+f"(d[i]) :: "memory");
}
__device__ __forceinline__ void ldsm4(uint32_t addr, uint32_t& r0, uint32_t& r1, uint32_t& r2, uint32_t& r3) {
  asm volatile("ldmatrix.sync.aligned.m8n8.x4.shared.b16 {%0, %1, %2, %3}, [%4];" : "=r"(r0), "=r"(r1), "=r"(r2), "=r"(r3) : "r"(addr) : "memory");
}
__device__ __forceinline__ void stsm4(uint32_t addr, uint32_t r0, uint32_t r1, uint32_t r2, uint32_t r3) {
  asm volatile("stmatrix.sync.aligned.m8n8.x4.shared.b16 [%0], {%1, %2, %3, %4};" :: "r"(addr), "r"(r0), "r"(r1), "r"(r2), "r"(r3) : "memory");
}
__device__ __forceinline__ uint32_t pack_bf16(float lo, float hi) {
  uint32_t r; asm("cvt.rn.bf16x2.f32 %0, %1, %2;" : "=r"(r) : "f"(hi), "f"(lo)); return r;
}
__device__ __forceinline__ float ex2(float x) { float y; asm("ex2.approx.ftz.f32 %0, %1;" : "=f"(y) : "f"(x)); return y; }
__device__ __forceinline__ float bf_lo(uint32_t v) { return __uint_as_float(v << 16); }
__device__ __forceinline__ float bf_hi(uint32_t v) { return __uint_as_float(v & 0xffff0000u); }
__device__ __forceinline__ float rbf(float x) { return __bfloat162float(__float2bfloat16_rn(x)); }

__device__ __forceinline__ uint32_t desc_lo(uint32_t addr) { return ((addr & 0x3FFFF) >> 4) | ((uint32_t)(HALF >> 4) << 16); }
__device__ __forceinline__ uint64_t desc(uint32_t lo) { return (uint64_t)lo | ((uint64_t)(64u | (1u << 30)) << 32); }

template<int TB> __device__ __forceinline__ void wgmma_ss_n128(float (&d)[64], uint64_t descA, uint64_t descB, int scaleD) {
  asm volatile("{\n.reg .pred p;\nsetp.ne.b32 p, %66, 0;\n"
    "wgmma.mma_async.sync.aligned.m64n128k16.f32.bf16.bf16 "
    "{%0, %1, %2, %3, %4, %5, %6, %7, %8, %9, %10, %11, %12, %13, %14, %15, "
    "%16, %17, %18, %19, %20, %21, %22, %23, %24, %25, %26, %27, %28, %29, %30, %31, "
    "%32, %33, %34, %35, %36, %37, %38, %39, %40, %41, %42, %43, %44, %45, %46, %47, "
    "%48, %49, %50, %51, %52, %53, %54, %55, %56, %57, %58, %59, %60, %61, %62, %63}, "
    "%64, %65, p, 1, 1, 0, %67;\n}\n"
    : "+f"(d[0]), "+f"(d[1]), "+f"(d[2]), "+f"(d[3]), "+f"(d[4]), "+f"(d[5]), "+f"(d[6]), "+f"(d[7]),
      "+f"(d[8]), "+f"(d[9]), "+f"(d[10]), "+f"(d[11]), "+f"(d[12]), "+f"(d[13]), "+f"(d[14]), "+f"(d[15]),
      "+f"(d[16]), "+f"(d[17]), "+f"(d[18]), "+f"(d[19]), "+f"(d[20]), "+f"(d[21]), "+f"(d[22]), "+f"(d[23]),
      "+f"(d[24]), "+f"(d[25]), "+f"(d[26]), "+f"(d[27]), "+f"(d[28]), "+f"(d[29]), "+f"(d[30]), "+f"(d[31]),
      "+f"(d[32]), "+f"(d[33]), "+f"(d[34]), "+f"(d[35]), "+f"(d[36]), "+f"(d[37]), "+f"(d[38]), "+f"(d[39]),
      "+f"(d[40]), "+f"(d[41]), "+f"(d[42]), "+f"(d[43]), "+f"(d[44]), "+f"(d[45]), "+f"(d[46]), "+f"(d[47]),
      "+f"(d[48]), "+f"(d[49]), "+f"(d[50]), "+f"(d[51]), "+f"(d[52]), "+f"(d[53]), "+f"(d[54]), "+f"(d[55]),
      "+f"(d[56]), "+f"(d[57]), "+f"(d[58]), "+f"(d[59]), "+f"(d[60]), "+f"(d[61]), "+f"(d[62]), "+f"(d[63])
    : "l"(descA), "l"(descB), "r"(scaleD), "n"(TB));
}

template<int TB> __device__ __forceinline__ void wgmma_rs_n128(float (&d)[64], uint32_t a0, uint32_t a1, uint32_t a2, uint32_t a3, uint64_t descB, int scaleD) {
  asm volatile("{\n.reg .pred p;\nsetp.ne.b32 p, %69, 0;\n"
    "wgmma.mma_async.sync.aligned.m64n128k16.f32.bf16.bf16 "
    "{%0, %1, %2, %3, %4, %5, %6, %7, %8, %9, %10, %11, %12, %13, %14, %15, "
    "%16, %17, %18, %19, %20, %21, %22, %23, %24, %25, %26, %27, %28, %29, %30, %31, "
    "%32, %33, %34, %35, %36, %37, %38, %39, %40, %41, %42, %43, %44, %45, %46, %47, "
    "%48, %49, %50, %51, %52, %53, %54, %55, %56, %57, %58, %59, %60, %61, %62, %63}, "
    "{%64, %65, %66, %67}, %68, p, 1, 1, %70;\n}\n"
    : "+f"(d[0]), "+f"(d[1]), "+f"(d[2]), "+f"(d[3]), "+f"(d[4]), "+f"(d[5]), "+f"(d[6]), "+f"(d[7]),
      "+f"(d[8]), "+f"(d[9]), "+f"(d[10]), "+f"(d[11]), "+f"(d[12]), "+f"(d[13]), "+f"(d[14]), "+f"(d[15]),
      "+f"(d[16]), "+f"(d[17]), "+f"(d[18]), "+f"(d[19]), "+f"(d[20]), "+f"(d[21]), "+f"(d[22]), "+f"(d[23]),
      "+f"(d[24]), "+f"(d[25]), "+f"(d[26]), "+f"(d[27]), "+f"(d[28]), "+f"(d[29]), "+f"(d[30]), "+f"(d[31]),
      "+f"(d[32]), "+f"(d[33]), "+f"(d[34]), "+f"(d[35]), "+f"(d[36]), "+f"(d[37]), "+f"(d[38]), "+f"(d[39]),
      "+f"(d[40]), "+f"(d[41]), "+f"(d[42]), "+f"(d[43]), "+f"(d[44]), "+f"(d[45]), "+f"(d[46]), "+f"(d[47]),
      "+f"(d[48]), "+f"(d[49]), "+f"(d[50]), "+f"(d[51]), "+f"(d[52]), "+f"(d[53]), "+f"(d[54]), "+f"(d[55]),
      "+f"(d[56]), "+f"(d[57]), "+f"(d[58]), "+f"(d[59]), "+f"(d[60]), "+f"(d[61]), "+f"(d[62]), "+f"(d[63])
    : "r"(a0), "r"(a1), "r"(a2), "r"(a3), "l"(descB), "r"(scaleD), "n"(TB));
}

template<int TB> __device__ __forceinline__ void wgmma_rs_n64(float (&d)[64], uint32_t a0, uint32_t a1, uint32_t a2, uint32_t a3, uint64_t descB, int scaleD) {
  asm volatile("{\n.reg .pred p;\nsetp.ne.b32 p, %37, 0;\n"
    "wgmma.mma_async.sync.aligned.m64n64k16.f32.bf16.bf16 "
    "{%0, %1, %2, %3, %4, %5, %6, %7, %8, %9, %10, %11, %12, %13, %14, %15, "
    "%16, %17, %18, %19, %20, %21, %22, %23, %24, %25, %26, %27, %28, %29, %30, %31}, "
    "{%32, %33, %34, %35}, %36, p, 1, 1, %38;\n}\n"
    : "+f"(d[0]), "+f"(d[1]), "+f"(d[2]), "+f"(d[3]), "+f"(d[4]), "+f"(d[5]), "+f"(d[6]), "+f"(d[7]),
      "+f"(d[8]), "+f"(d[9]), "+f"(d[10]), "+f"(d[11]), "+f"(d[12]), "+f"(d[13]), "+f"(d[14]), "+f"(d[15]),
      "+f"(d[16]), "+f"(d[17]), "+f"(d[18]), "+f"(d[19]), "+f"(d[20]), "+f"(d[21]), "+f"(d[22]), "+f"(d[23]),
      "+f"(d[24]), "+f"(d[25]), "+f"(d[26]), "+f"(d[27]), "+f"(d[28]), "+f"(d[29]), "+f"(d[30]), "+f"(d[31])
    : "r"(a0), "r"(a1), "r"(a2), "r"(a3), "l"(descB), "r"(scaleD), "n"(TB));
}

struct Cur {
  uint32_t o, phase;
  __device__ __forceinline__ void adv() { o += 8; if (o == 8 * NSLOT) { o = 0; phase ^= 1; } }
};

struct Params {
  CUtensorMap ckv, xn, x, wq, wuk, wuv, wo;
  __nv_bfloat16* out;
  const __nv_bfloat16 *pwo, *px, *w_r, *w_gate, *w_up, *w_down;
  float neg;
  uint32_t zero;
};

__device__ __forceinline__ void moe_cta(const Params& P, int q, unsigned ep, uint8_t* smem) {
  float* xs = (float*)smem;
  float* red = xs + DM;
  float* hs = red + 2 * 8 * 344;
  float* sv = hs + 344; int* si = (int*)(sv + 16);
  const int tid = threadIdx.x, lane = tid & 31, warp = tid >> 5;
  if (tid < 16) flag_wait(F_LN + tid, ep * 8);
  __syncthreads();
  float bv = -INFINITY; int bi = 0x7fffffff;
  for (int i = tid; i < SEQ; i += 384) { float v = __ldcg(&g_r[i]); if (v > bv || bi == 0x7fffffff) { bv = v; bi = i; } }
#pragma unroll
  for (int o = 16; o; o >>= 1) {
    float ov = __shfl_xor_sync(~0u, bv, o); int oi = __shfl_xor_sync(~0u, bi, o);
    if (ov > bv || (ov == bv && oi < bi)) { bv = ov; bi = oi; }
  }
  if (lane == 0) { sv[warp] = bv; si[warp] = bi; }
  __syncthreads();
  bv = sv[0]; bi = si[0];
  for (int w = 1; w < 12; w++) { float ov = sv[w]; int oi = si[w]; if (ov > bv || (ov == bv && oi < bi)) { bv = ov; bi = oi; } }
  for (int i = tid; i < DM; i += 384) xs[i] = __bfloat162float(__ldcg(&g_xn[bi * DM + i]));
  __syncthreads();
  const int f0 = q * 344;
  if (tid < 344) {
    const int cg = tid % 43, ksl = tid / 43;
    float ag[8], au[8];
#pragma unroll
    for (int i = 0; i < 8; i++) ag[i] = au[i] = 0.f;
    const __nv_bfloat16* pg = P.w_gate + (size_t)(ksl * 64) * FF + f0 + cg * 8;
    const __nv_bfloat16* pu = P.w_up + (size_t)(ksl * 64) * FF + f0 + cg * 8;
#pragma unroll 8
    for (int k = 0; k < 64; k++) {
      uint4 a = __ldg((const uint4*)(pg + (size_t)k * FF)), b = __ldg((const uint4*)(pu + (size_t)k * FF));
      float xv = xs[ksl * 64 + k];
      ag[0] += xv * bf_lo(a.x); ag[1] += xv * bf_hi(a.x); ag[2] += xv * bf_lo(a.y); ag[3] += xv * bf_hi(a.y);
      ag[4] += xv * bf_lo(a.z); ag[5] += xv * bf_hi(a.z); ag[6] += xv * bf_lo(a.w); ag[7] += xv * bf_hi(a.w);
      au[0] += xv * bf_lo(b.x); au[1] += xv * bf_hi(b.x); au[2] += xv * bf_lo(b.y); au[3] += xv * bf_hi(b.y);
      au[4] += xv * bf_lo(b.z); au[5] += xv * bf_hi(b.z); au[6] += xv * bf_lo(b.w); au[7] += xv * bf_hi(b.w);
    }
#pragma unroll
    for (int i = 0; i < 8; i++) { red[ksl * 344 + cg * 8 + i] = ag[i]; red[(8 + ksl) * 344 + cg * 8 + i] = au[i]; }
  }
  __syncthreads();
  if (tid < 344) {
    float g = 0.f, u = 0.f;
#pragma unroll
    for (int i = 0; i < 8; i++) { g += red[i * 344 + tid]; u += red[(8 + i) * 344 + tid]; }
    g = rbf(g); u = rbf(u);
    g = rbf(g / (1.f + expf(-g)));
    hs[tid] = rbf(g * u);
  }
  __syncthreads();
  {
    const int cg = tid & 63, fs = tid >> 6;
    float ay[8];
#pragma unroll
    for (int i = 0; i < 8; i++) ay[i] = 0.f;
    const __nv_bfloat16* pd = P.w_down + (size_t)f0 * DM + cg * 8;
#pragma unroll 8
    for (int f = fs; f < 344; f += 6) {
      uint4 a = __ldg((const uint4*)(pd + (size_t)f * DM));
      float hv = hs[f];
      ay[0] += hv * bf_lo(a.x); ay[1] += hv * bf_hi(a.x); ay[2] += hv * bf_lo(a.y); ay[3] += hv * bf_hi(a.y);
      ay[4] += hv * bf_lo(a.z); ay[5] += hv * bf_hi(a.z); ay[6] += hv * bf_lo(a.w); ay[7] += hv * bf_hi(a.w);
    }
#pragma unroll
    for (int i = 0; i < 8; i++) red[fs * DM + cg * 8 + i] = ay[i];
  }
  __syncthreads();
  for (int i = tid; i < DM; i += 384) {
    float y = 0.f;
#pragma unroll
    for (int s = 0; s < 6; s++) y += red[s * DM + i];
    g_ypart[q * DM + i] = y;
  }
  if (q == 0 && tid == 0) { g_sel = bi; g_gate = rbf(1.f / (1.f + expf(-bv))); }
  __syncthreads();
  if (tid == 0) { __threadfence(); flag_add(F_MOE); }
}

__device__ __forceinline__ float half_sum(float v) {
#pragma unroll
  for (int o = 8; o; o >>= 1) v += __shfl_xor_sync(~0u, v, o);
  return v;
}
__device__ __forceinline__ void ln_row(const Params& P, int row, int l16, const uint4 (&xi)[4], const uint4 (&wi)[4]) {
  uint32_t x[16], w[16];
#pragma unroll
  for (int i = 0; i < 4; i++) {
    x[4 * i] = xi[i].x; x[4 * i + 1] = xi[i].y; x[4 * i + 2] = xi[i].z; x[4 * i + 3] = xi[i].w;
    w[4 * i] = wi[i].x; w[4 * i + 1] = wi[i].y; w[4 * i + 2] = wi[i].z; w[4 * i + 3] = wi[i].w;
  }
  float s[4] = {0.f, 0.f, 0.f, 0.f};
#pragma unroll
  for (int k = 0; k < 16; k++) { s[k & 1] += bf_lo(x[k]); s[2 + (k & 1)] += bf_hi(x[k]); }
  const float mean = half_sum((s[0] + s[1]) + (s[2] + s[3])) * (1.f / DM);
  s[0] = s[1] = s[2] = s[3] = 0.f;
#pragma unroll
  for (int k = 0; k < 16; k++) {
    const float d0 = bf_lo(x[k]) - mean, d1 = bf_hi(x[k]) - mean;
    s[k & 1] = fmaf(d0, d0, s[k & 1]); s[2 + (k & 1)] = fmaf(d1, d1, s[2 + (k & 1)]);
  }
  const float var = half_sum((s[0] + s[1]) + (s[2] + s[3])) * (1.f / DM);
  const uint32_t mb = pack_bf16(mean, mean);
  const float rs = __frcp_rn(rbf(__fsqrt_rn(rbf(rbf(var) + 1e-5f))));
  s[0] = s[1] = s[2] = s[3] = 0.f;
#pragma unroll
  for (int k = 0; k < 16; k++) {
    uint32_t d;
    asm("sub.rn.bf16x2 %0, %1, %2;" : "=r"(d) : "r"(x[k]), "r"(mb));
    x[k] = pack_bf16(bf_lo(d) * rs, bf_hi(d) * rs);
    s[k & 1] = fmaf(bf_lo(x[k]), bf_lo(w[k]), s[k & 1]); s[2 + (k & 1)] = fmaf(bf_hi(x[k]), bf_hi(w[k]), s[2 + (k & 1)]);
  }
  uint4* dst = (uint4*)(g_xn + (size_t)row * DM) + l16;
#pragma unroll
  for (int i = 0; i < 4; i++) dst[16 * i] = make_uint4(x[4 * i], x[4 * i + 1], x[4 * i + 2], x[4 * i + 3]);
  const float r = half_sum((s[0] + s[1]) + (s[2] + s[3]));
  if (l16 == 0) g_r[row] = rbf(r);
}

struct Ctx {
  uint32_t sb;
  uint32_t dlo;
  uint32_t full0;
  uint32_t rel;
  bool rel_pred, warp0;
  uint32_t stg;
  uint32_t stg_full, stg_empty;
  uint32_t stg_phase;
  uint32_t frag_off;
  uint32_t frag_x;
  int w;
  float neg;
  uint32_t zero;
  __device__ __forceinline__ void wait(const Cur& c) const { mbar_wait(full0 + c.o, c.phase); }
  __device__ __forceinline__ void release(const Cur& c) const { mbar_arrive_cluster_if(rel + c.o, rel_pred); }
  __device__ __forceinline__ void skip(const Cur& c) const { if (warp0) { wait(c); release(c); } }
  __device__ __forceinline__ uint32_t addr(const Cur& c) const { return sb + c.o * (TILE / 8); }
  __device__ __forceinline__ uint32_t dsc(const Cur& c) const { return dlo + c.o * (TILE / 128); }
  __device__ __forceinline__ void turn_begin() const { bar_sync(1 + w, 256); }
  __device__ __forceinline__ void turn_end() const { bar_arrive(2 - w, 256); }
  __device__ __forceinline__ uint32_t frag(int jj, int hstride) const { return (jj >> 2) * hstride + frag_off + (((jj & 3) * 32) ^ frag_x); }
  template <bool SCALE> __device__ __forceinline__ void stage_out(const float (&d)[64], float s0, float s1) {
    mbar_wait(stg_empty, stg_phase ^ 1);
    stg_phase ^= 1;
#pragma unroll
    for (int jj = 0; jj < 8; jj++) {
      if (SCALE)
        stsm4(stg + frag(jj, 8192), pack_bf16(d[8 * jj] * s0, d[8 * jj + 1] * s0), pack_bf16(d[8 * jj + 2] * s1, d[8 * jj + 3] * s1),
              pack_bf16(d[8 * jj + 4] * s0, d[8 * jj + 5] * s0), pack_bf16(d[8 * jj + 6] * s1, d[8 * jj + 7] * s1));
      else
        stsm4(stg + frag(jj, 8192), pack_bf16(d[8 * jj], d[8 * jj + 1]), pack_bf16(d[8 * jj + 2], d[8 * jj + 3]),
              pack_bf16(d[8 * jj + 4], d[8 * jj + 5]), pack_bf16(d[8 * jj + 6], d[8 * jj + 7]));
    }
  }
  __device__ __forceinline__ void publish() const { fence_async_smem(); mbar_arrive(stg_full); }
};

constexpr float SM_SCALE = 0.08838834764831845f * 1.4426950408889634f;
constexpr float SUM_LIMIT = 1152921504606846976.f;

struct Attn {
  float o[64], s[64];
  uint32_t p[32], q[32];
  float n0, n1;
  float l0, l1;
};

__device__ __forceinline__ void issue_qk(Attn& A, uint32_t d) {
#pragma unroll
  for (int kk = 0; kk < 8; kk++)
    wgmma_rs_n128<0>(A.s, A.q[4 * kk], A.q[4 * kk + 1], A.q[4 * kk + 2], A.q[4 * kk + 3], desc(d + (((kk >> 2) * HALF + (kk & 3) * 32) >> 4)), kk > 0);
  wg_commit();
}
__device__ __forceinline__ void issue_pv(Attn& A, uint32_t d, int acc) {
#pragma unroll
  for (int kk = 0; kk < 8; kk++)
    wgmma_rs_n128<1>(A.o, A.p[4 * kk], A.p[4 * kk + 1], A.p[4 * kk + 2], A.p[4 * kk + 3], desc(d + ((kk * 2048) >> 4)), kk > 0 ? 1 : acc);
  wg_commit();
}
__device__ __forceinline__ void pack_p(Attn& A) {
#pragma unroll
  for (int i = 0; i < 32; i++) A.p[i] = pack_bf16(A.s[2 * i], A.s[2 * i + 1]);
}
__device__ __forceinline__ void block_max(const Attn& A, float& n0, float& n1) {
  float x0 = fmaxf(A.s[0], A.s[1]), x1 = fmaxf(A.s[2], A.s[3]);
  float y0 = fmaxf(A.s[4], A.s[5]), y1 = fmaxf(A.s[6], A.s[7]);
#pragma unroll
  for (int j = 2; j < 16; j += 2) {
    x0 = fmaxf(x0, fmaxf(A.s[4 * j], A.s[4 * j + 1])); x1 = fmaxf(x1, fmaxf(A.s[4 * j + 2], A.s[4 * j + 3]));
    y0 = fmaxf(y0, fmaxf(A.s[4 * j + 4], A.s[4 * j + 5])); y1 = fmaxf(y1, fmaxf(A.s[4 * j + 6], A.s[4 * j + 7]));
  }
  x0 = fmaxf(x0, y0); x1 = fmaxf(x1, y1);
  x0 = fmaxf(x0, __shfl_xor_sync(~0u, x0, 1)); x1 = fmaxf(x1, __shfl_xor_sync(~0u, x1, 1));
  x0 = fmaxf(x0, __shfl_xor_sync(~0u, x0, 2)); x1 = fmaxf(x1, __shfl_xor_sync(~0u, x1, 2));
  n0 = -x0 * SM_SCALE; n1 = -x1 * SM_SCALE;
}
template <int J0, int J1> __device__ __forceinline__ void exp_cols(Attn& A, float (&a)[4]) {
#pragma unroll
  for (int j = J0; j < J1; j++) {
    A.s[4 * j] = ex2(fmaf(A.s[4 * j], SM_SCALE, A.n0)); A.s[4 * j + 1] = ex2(fmaf(A.s[4 * j + 1], SM_SCALE, A.n0));
    A.s[4 * j + 2] = ex2(fmaf(A.s[4 * j + 2], SM_SCALE, A.n1)); A.s[4 * j + 3] = ex2(fmaf(A.s[4 * j + 3], SM_SCALE, A.n1));
    if (j == 0) { a[0] = A.s[0]; a[1] = A.s[1]; a[2] = A.s[2]; a[3] = A.s[3]; }
    else { a[0] += A.s[4 * j]; a[1] += A.s[4 * j + 1]; a[2] += A.s[4 * j + 2]; a[3] += A.s[4 * j + 3]; }
  }
}
__device__ __forceinline__ void pin(float v, float neg, uint32_t addr) {
  asm volatile("{\n.reg .pred p;\nsetp.lt.f32 p, %0, %2;\n@p mbarrier.arrive.shared::cta.b64 _, [%1];\n}" :: "f"(v), "r"(addr), "f"(neg) : "memory");
}
__device__ __forceinline__ void causal_mask(Attn& A, int rel) {
#pragma unroll
  for (int j = 0; j < 16; j++) {
    if (8 * j > rel) A.s[4 * j] = -INFINITY;
    if (8 * j + 1 > rel) A.s[4 * j + 1] = -INFINITY;
    if (8 * j > rel + 8) A.s[4 * j + 2] = -INFINITY;
    if (8 * j + 1 > rel + 8) A.s[4 * j + 3] = -INFINITY;
  }
}
__device__ __forceinline__ void finish_item(Ctx& C, Attn& A, float l0, float l1) {
  l0 += __shfl_xor_sync(~0u, l0, 1); l1 += __shfl_xor_sync(~0u, l1, 1);
  l0 += __shfl_xor_sync(~0u, l0, 2); l1 += __shfl_xor_sync(~0u, l1, 2);
  C.stage_out<true>(A.o, __fdividef(1.f, l0), __fdividef(1.f, l1));
}
__device__ __forceinline__ void redo_block(Attn& A, const uint8_t* ktile, bool diag, int rel, uint32_t zero) {
  const int lane = threadIdx.x & 31;
  uint32_t off = (lane >> 2) * 144 + (lane & 3) * 4;
#pragma unroll
  for (int j = 0; j < 16; j++) {
    float c0 = 0.f, c1 = 0.f, c2 = 0.f, c3 = 0.f;
    if (j > 0) off += __float_as_uint(A.s[4 * j - 4]) & zero;
#pragma unroll
    for (int kk = 0; kk < 8; kk++) {
      const uint32_t b0 = __ldcg((const uint32_t*)(ktile + (off ^ ((kk & 3) * 32)) + j * 1024 + (kk >> 2) * HALF));
      const uint32_t b1 = __ldcg((const uint32_t*)(ktile + (off ^ ((kk & 3) * 32 + 16)) + j * 1024 + (kk >> 2) * HALF));
      asm volatile("mma.sync.aligned.m16n8k16.row.col.f32.bf16.bf16.f32 {%0, %1, %2, %3}, {%4, %5, %6, %7}, {%8, %9}, {%0, %1, %2, %3};"
                   : "+f"(c0), "+f"(c1), "+f"(c2), "+f"(c3)
                   : "r"(A.q[4 * kk]), "r"(A.q[4 * kk + 1]), "r"(A.q[4 * kk + 2]), "r"(A.q[4 * kk + 3]), "r"(b0), "r"(b1) : "memory");
    }
    A.s[4 * j] = c0; A.s[4 * j + 1] = c1; A.s[4 * j + 2] = c2; A.s[4 * j + 3] = c3;
  }
  if (diag) causal_mask(A, rel);
  float n0, n1, a[4];
  block_max(A, n0, n1);
  n0 = fminf(n0, A.n0); n1 = fminf(n1, A.n1);
  const float c0 = ex2(n0 - A.n0), c1 = ex2(n1 - A.n1);
  A.n0 = n0; A.n1 = n1;
  exp_cols<0, 16>(A, a);
  A.l0 = fmaf(A.l0, c0, a[0] + a[1]); A.l1 = fmaf(A.l1, c1, a[2] + a[3]);
#pragma unroll
  for (int j = 0; j < 16; j++) { A.o[4 * j] *= c0; A.o[4 * j + 1] *= c0; A.o[4 * j + 2] *= c1; A.o[4 * j + 3] *= c1; }
  pack_p(A);
}
template <bool HAS_PREV> __device__ __forceinline__ void item_begin(Ctx& C, Attn& A, Cur& cur, bool skip, int pv_acc, bool pub, bool diag, int rel) {
  Cur cq, ck, cv, cs;
  if (HAS_PREV && skip) { C.skip(cur); cur.adv(); cv = cur; cur.adv(); }
  if (HAS_PREV) { cq = cur; cur.adv(); }
  ck = cur; cur.adv();
  if (HAS_PREV) {
    cs = cur; cur.adv(); if (!skip) cv = cs;
    C.wait(cq);
    const uint32_t qa = C.addr(cq) + C.w * 8192;
#pragma unroll
    for (int jj = 0; jj < 8; jj++) ldsm4(qa + C.frag(jj, HALF), A.q[4 * jj], A.q[4 * jj + 1], A.q[4 * jj + 2], A.q[4 * jj + 3]);
  }
  C.wait(ck);
  C.turn_begin();
  wg_fence();
  issue_qk(A, C.dsc(ck));
  if (HAS_PREV) { C.wait(cv); wg_fence(); issue_pv(A, C.dsc(cv), pv_acc); }
  C.turn_end();
  if (pub) C.publish();
  if (HAS_PREV) wg_wait<1>(); else wg_wait<0>();
  reg_fence(A.s);
  if (HAS_PREV) C.release(cq);
  C.release(ck);
  if (diag) causal_mask(A, rel);
  block_max(A, A.n0, A.n1);
  if (HAS_PREV) {
    wg_wait<0>();
    reg_fence(A.o);
    C.release(cv);
    finish_item(C, A, A.l0, A.l1);
  }
  float a[4];
  exp_cols<0, 16>(A, a);
  A.l0 = a[0] + a[1]; A.l1 = a[2] + a[3];
  pack_p(A);
  if (HAS_PREV && skip) C.skip(cs);
}
__device__ __forceinline__ void item_step(Ctx& C, Attn& A, Cur& cur, int pv_acc, bool pub, bool diag, int rel, const uint8_t* ktile) {
  const Cur ck = cur; cur.adv();
  const Cur cv = cur; cur.adv();
  C.wait(ck);
  C.turn_begin();
  wg_fence();
  issue_qk(A, C.dsc(ck));
  C.wait(cv);
  wg_fence();
  issue_pv(A, C.dsc(cv), pv_acc);
  C.turn_end();
  if (pub) C.publish();
  wg_wait<1>();
  reg_fence(A.s);
  C.release(ck);
  if (diag) causal_mask(A, rel);
  float a[4];
  exp_cols<0, 8>(A, a);
  pin((a[0] + a[1]) + (a[2] + a[3]), C.neg, C.stg_full);
  wg_wait<0>();
  reg_fence(A.o);
  C.release(cv);
  exp_cols<8, 16>(A, a);
  pack_p(A);
  const float b0 = a[0] + a[1], b1 = a[2] + a[3];
  if (__builtin_expect(__any_sync(~0u, !(b0 + b1 <= SUM_LIMIT)), 0)) redo_block(A, ktile, diag, rel, C.zero);
  else { A.l0 += b0; A.l1 += b1; }
}

template <bool LOAD_A> __device__ __forceinline__ void proj_unit(Ctx& C, Cur& cur, uint32_t (&a)[128], float (&acc)[64], bool pub) {
#pragma unroll
  for (int i = 0; i < 4; i++) {
    Cur ca = cur;
    if (LOAD_A) {
      cur.adv();
      C.wait(ca);
      const uint32_t aa = C.addr(ca) + C.w * 8192;
#pragma unroll
      for (int jj = 0; jj < 8; jj++) ldsm4(aa + C.frag(jj, HALF), a[32 * i + 4 * jj], a[32 * i + 4 * jj + 1], a[32 * i + 4 * jj + 2], a[32 * i + 4 * jj + 3]);
    }
    const Cur cb = cur; cur.adv();
    C.wait(cb);
    C.turn_begin();
    wg_fence();
    const uint32_t d = C.dsc(cb);
#pragma unroll
    for (int kk = 0; kk < 8; kk++)
      wgmma_rs_n128<1>(acc, a[32 * i + 4 * kk], a[32 * i + 4 * kk + 1], a[32 * i + 4 * kk + 2], a[32 * i + 4 * kk + 3], desc(d + ((kk * 2048) >> 4)), (i | kk) > 0);
    wg_commit();
    C.turn_end();
    if (i == 0 && pub) C.publish();
    wg_wait<0>();
    reg_fence(acc);
    if (LOAD_A) C.release(ca);
    C.release(cb);
  }
}

__global__ void __cluster_dims__(2, 1, 1) __launch_bounds__(384, 1) fused_kernel(const __grid_constant__ Params P) {
  extern __shared__ uint8_t smem_raw[];
  uint8_t* smem = smem_raw + ((1024 - (smem_u32(smem_raw) & 1023)) & 1023);
  const int tid = threadIdx.x;
  const int c = blockIdx.x >> 1, r = blockIdx.x & 1;
  const unsigned ep = g_epoch[blockIdx.x] + 1;
  if (c >= 64) {
    moe_cta(P, blockIdx.x - 128, ep, smem);
    if (tid == 0) g_epoch[blockIdx.x] = ep;
    return;
  }
  const int rp = c & 7, g = c >> 3;
  const int rb = 2 * rp + r;
  const int j3 = c & 15, ks = c >> 5, ncol = 2 * ((c >> 4) & 1) + r;
  const uint32_t sb = smem_u32(smem);
  const uint32_t full0 = sb + SMEM_BAR, empty0 = full0 + 8 * NSLOT, stgf0 = empty0 + 8 * NSLOT, stge0 = stgf0 + 16;
  if (tid == 0) {
    for (int i = 0; i < NSLOT; i++) { mbar_init(full0 + 8 * i, 1); mbar_init(empty0 + 8 * i, 4); }
    for (int i = 0; i < 2; i++) { mbar_init(stgf0 + 8 * i, 128); mbar_init(stge0 + 8 * i, 1); }
    asm volatile("fence.mbarrier_init.release.cluster;" ::: "memory");
  }
  __syncwarp();
  asm volatile("barrier.cluster.arrive.relaxed.aligned;" ::: "memory");
  if (tid == 0) {
    mbar_expect(full0, TILE);
    tma_load(sb, &P.ckv, 0, rb * 128, full0);
    tma_load(sb + HALF, &P.ckv, 64, rb * 128, full0);
    asm volatile("prefetch.tensormap [%0];" :: "l"(&P.wuk) : "memory");
  }
  const int ln_r = rb * 128 + 16 * g + ((tid >> 4) & 15);
  uint4 ln_x[4], ln_w[4];
#pragma unroll
  for (int i = 0; i < 4; i++) {
    ln_x[i] = __ldg((const uint4*)(P.px + (size_t)ln_r * DM) + 16 * i + (tid & 15));
    ln_w[i] = __ldg((const uint4*)P.w_r + 16 * i + (tid & 15));
  }
  __syncwarp();
  asm volatile("barrier.cluster.wait.aligned;" ::: "memory");
  const int wg = __shfl_sync(~0u, tid >> 7, 0);

  if (wg == 0) {
    asm volatile("setmaxnreg.dec.sync.aligned.u32 40;");
    const int warp = tid >> 5;
    if (warp == 0) {
      if (tid == 0) {
        Cur cur{8, 0};
        uint32_t dst, bar;
        auto acquire = [&]() {
          mbar_wait(empty0 + cur.o, cur.phase ^ 1);
          dst = sb + cur.o * (TILE / 8); bar = full0 + cur.o;
          mbar_expect(bar, TILE);
          cur.adv();
        };
        for (int u = 0; u < 12; u++) {
          const CUtensorMap* wm = u >= 8 ? &P.wq : ((u & 1) ? &P.wuv : &P.wuk);
          const CUtensorMap* am = u >= 8 ? &P.xn : &P.ckv;
          const int head = 4 * g + (u >= 8 ? (0x0231 >> (4 * (u - 8))) & 3 : u >> 1);
          if (u == 8) { flag_wait(F_LN + rb, ep * 8); fence_async_all(); }
          for (int i = 0; i < 4; i++) {
            if ((u & 7) == 0 && (u | i)) {
              acquire();
              tma_load(dst, am, 128 * i, rb * 128, bar);
              tma_load(dst + HALF, am, 128 * i + 64, rb * 128, bar);
            }
            acquire();
            tma_load_mc(dst + r * HALF, wm, head * 128 + 64 * r, 128 * i, bar);
          }
        }
        const uint8_t* prev_v = nullptr;
        for (int it = 0; it < 4; it++) {
          const int head = 4 * g + it;
          const int j = (it & 1) ? 15 - rb : rb;
          if (it < 3) { flag_wait(F_GRP + 3 * g + it, ep * 32); fence_async_all(); }
          else asm volatile("cp.async.bulk.prefetch.L2.global [%0], %1;" :: "l"(P.pwo + (size_t)blockIdx.x * (TILE / 2)), "r"(TILE) : "memory");
          if (it > 0) {
            acquire();
            bulk_load(dst, g_qkv + (size_t)(head * 16 + j) * TILE, TILE, bar);
          }
          for (int b = 0; b <= (j | 1); b++) {
            acquire();
            bulk_load_mc(dst + r * HALF, g_qkv + (size_t)((NH + head) * 16 + b) * TILE + r * HALF, HALF, bar);
            if (prev_v) { acquire(); bulk_load_mc(dst + r * HALF, prev_v, HALF, bar); }
            prev_v = g_qkv + (size_t)((2 * NH + head) * 16 + b) * TILE + r * HALF;
          }
        }
        acquire(); bulk_load_mc(dst + r * HALF, prev_v, HALF, bar);
        for (int t = 0; t < 16; t++) {
          const int head = 16 * ks + 4 * ((t & 7) >> 1) + 2 * (t >> 3) + (t & 1);
          acquire();
          tma_load(dst + ks * HALF, &P.wo, ncol * 128, head * 128, bar);
          tma_load(dst + (ks ^ 1) * HALF, &P.wo, ncol * 128 + 64, head * 128, bar);
          if ((t & 7) == 0) { flag_wait(F_CTX + j3 * 4 + ks * 2 + (t >> 3), ep * 16); fence_async_all(); }
          acquire();
          bulk_load_mc(dst + r * HALF, g_qkv + (size_t)(head * 16 + j3) * TILE + r * HALF, HALF, bar);
          if (t == 0) { flag_wait(F_LN + j3, ep * 8); flag_wait(F_MOE, ep * 4); }
        }
        acquire();
        tma_load(dst, &P.x, ncol * 128 + 64 * ks, j3 * 128, bar);
        tma_load(dst + HALF, &P.xn, ncol * 128 + 64 * ks, j3 * 128, bar);
        for (int i = 0; i < NSLOT; i++) { mbar_wait(empty0 + cur.o, cur.phase ^ 1); cur.adv(); }
        g_epoch[blockIdx.x] = ep;
      }
    } else if (warp == 3) {
      bar_sync(3, 288);
      if (tid == 96) { __threadfence(); fence_async_all(); flag_add(F_LN + rb); }
    } else {
      if ((tid & 31) == 0) {
        const int w = warp - 1;
        const uint32_t stg = sb + SMEM_STG + w * HALF;
        for (int job = 0; job < 15; job++) {
          int tile, flag = -1;
          if (job < 8) {
            tile = ((1 + (job & 1)) * NH + 4 * g + (job >> 1)) * 16 + rb;
            if (job == 3) flag = F_GRP + 3 * g;
          } else if (job < 11) {
            tile = (4 * g + ((0x231 >> (4 * (job - 8))) & 3)) * 16 + rb;
            if (job != 9) flag = F_GRP + 3 * g + (job >> 1) - 3;
          } else {
            const int it = job - 11;
            const int j = (it & 1) ? 15 - rb : rb;
            tile = (4 * g + it) * 16 + j;
            flag = F_CTX + j * 4 + (g >> 2) * 2 + (it >> 1);
          }
          uint8_t* d = g_qkv + (size_t)tile * TILE + w * 8192;
          mbar_wait(stgf0 + 8 * w, job & 1);
          bulk_store(d, stg, 8192);
          bulk_store(d + HALF, stg + 8192, 8192);
          asm volatile("cp.async.bulk.commit_group;" ::: "memory");
          asm volatile("cp.async.bulk.wait_group.read 0;" ::: "memory");
          mbar_arrive(stge0 + 8 * w);
          if (flag >= 0) {
            if (job == 3) asm volatile("cp.async.bulk.wait_group 2;" ::: "memory");
            else asm volatile("cp.async.bulk.wait_group 0;" ::: "memory");
            fence_async_all();
            flag_add(flag);
          }
          if (w == 1 && (job == 8 || job == 10 || job >= 13)) TLX(job == 8 ? 28 : job == 10 ? 29 : 17 + job);
        }
      }
    }
  } else {
    asm volatile("setmaxnreg.inc.sync.aligned.u32 232;");
    const int t = tid & 127, lane = tid & 31, wi = t >> 5;
    Ctx C;
    C.neg = P.neg; C.zero = P.zero; C.sb = sb; C.dlo = desc_lo(sb); C.full0 = full0; C.w = wg - 1;
    asm("mapa.shared::cluster.u32 %0, %1, %2;" : "=r"(C.rel) : "r"(empty0), "r"(lane & 1));
    C.rel_pred = t < 2;
    C.warp0 = __shfl_sync(~0u, wi, 0) == 0;
    C.stg = sb + SMEM_STG + C.w * HALF;
    C.stg_full = stgf0 + 8 * C.w; C.stg_empty = stge0 + 8 * C.w; C.stg_phase = 0;
    C.frag_off = (16 * wi + (lane & 15)) * 128;
    C.frag_x = ((lane >> 4) ^ (lane & 7)) * 16;
    TL(C.w * 16 + 0);
    ln_row(P, ln_r, tid & 15, ln_x, ln_w);
    bar_arrive(3, 288);
    if (C.w == 1) bar_arrive(1, 256);
    Cur cur{0, 0};
    Attn A;
    TL(C.w * 16 + 1);
    {
      uint32_t a[128];
      float acc[64];
#pragma unroll 1
      for (int half = 0; half < 2; half++) {
        if (half) C.stage_out<false>(acc, 1.f, 1.f);
        proj_unit<true>(C, cur, a, acc, half);
        TL(half ? 13 + C.w * 2 : 2 + C.w * 16);
#pragma unroll 1
        for (int u = half ? 5 : 1; u < 8; u++) {
          C.stage_out<false>(acc, 1.f, 1.f);
          proj_unit<false>(C, cur, a, acc, true);
        }
        if (half == 0) TL(12 + C.w * 2);
      }
#pragma unroll
      for (int i = 0; i < 32; i++) A.q[i] = pack_bf16(acc[2 * i], acc[2 * i + 1]);
    }
    TL(C.w * 16 + 3);
    {
      const int rel = 64 * C.w + 16 * wi + (lane >> 2) - 2 * (lane & 3);
      A.l0 = A.l1 = 0.f;
      int pv_acc = 0;
      bool skip = false, pub = false;
#pragma unroll 1
      for (int it = 0; it < 4; it++) {
        const int j = (it & 1) ? 15 - rb : rb;
        if (it == 0) item_begin<false>(C, A, cur, false, 0, false, j == 0, rel);
        else item_begin<true>(C, A, cur, skip, pv_acc, pub, j == 0, rel);
        pv_acc = 0; pub = it > 0; skip = !(j & 1);
        const uint8_t* kt = g_qkv + (size_t)((NH + 4 * g + it) * 16) * TILE;
#pragma unroll 1
        for (int b = 1; b <= j; b++) { item_step(C, A, cur, pv_acc, pub, b == j, rel, kt + (size_t)b * TILE); pv_acc = 1; pub = false; }
        TL(C.w * 16 + 4 + it);
      }
      if (skip) { C.skip(cur); cur.adv(); }
      const Cur cv = cur; cur.adv();
      C.wait(cv);
      C.turn_begin();
      wg_fence();
      issue_pv(A, C.dsc(cv), pv_acc);
      C.turn_end();
      if (pub) C.publish();
      wg_wait<0>();
      reg_fence(A.o);
      C.release(cv);
      finish_item(C, A, A.l0, A.l1);
      C.publish();
      if (skip) { C.skip(cur); cur.adv(); }
      if (C.w == 0) C.turn_begin();
    }
    TL(C.w * 16 + 8);
    {
      float acc[64];
      Cur pb = cur, pa = cur;
#pragma unroll 1
      for (int h = 0; h < 16; h++) {
        const Cur cb = cur; cur.adv();
        const Cur ca = cur; cur.adv();
        C.wait(cb); C.wait(ca);
        wg_fence();
        const uint32_t da = C.dsc(ca) + C.w * 512, db = C.dsc(cb);
#pragma unroll
        for (int kk = 0; kk < 8; kk++)
          wgmma_ss_n128<1>(acc, desc(da + (((kk >> 2) * HALF + (kk & 3) * 32) >> 4)), desc(db + ((kk * 2048) >> 4)), kk > 0 ? 1 : h);
        wg_commit();
        wg_wait<1>();
        if (h > 0) { C.release(pb); C.release(pa); }
        pb = cb; pa = ca;
      }
      const int sel = __ldcg(&g_sel);
      wg_wait<0>();
      reg_fence(acc);
      C.release(pb); C.release(pa);
      TL(C.w * 16 + 9);
      uint4* mine = g_part + (size_t)(blockIdx.x * 2 + C.w) * (11 * 128) + t;
      const uint4* theirs = g_part + (size_t)((blockIdx.x ^ 64) * 2 + C.w) * (11 * 128) + t;
#pragma unroll
      for (int i = 0; i < 11; i++) st_tagged(mine + i * 128, acc[32 + 3 * i], acc[33 + 3 * i], i < 10 ? acc[34 + 3 * i] : 0.f, ep);
      const Cur cr = cur;
      C.wait(cr);
      uint32_t xr[16], nr[16];
      const uint32_t xa = C.addr(cr) + C.w * 8192;
#pragma unroll
      for (int jj = 0; jj < 4; jj++) {
        ldsm4(xa + C.frag(jj, 0), xr[4 * jj], xr[4 * jj + 1], xr[4 * jj + 2], xr[4 * jj + 3]);
        ldsm4(xa + HALF + C.frag(jj, 0), nr[4 * jj], nr[4 * jj + 1], nr[4 * jj + 2], nr[4 * jj + 3]);
      }
      C.release(cr);
      const int row0 = j3 * 128 + 64 * C.w + 16 * wi + (lane >> 2);
      if (sel == row0 || sel == row0 + 8) {
        const float gate = __ldcg(&g_gate);
        const float* yp = g_ypart + ncol * 128 + 64 * ks + 2 * (lane & 3);
#pragma unroll
        for (int j = 0; j < 8; j++) {
          float y0 = 0.f, y1 = 0.f;
#pragma unroll
          for (int q = 0; q < 4; q++) { y0 += __ldcg(yp + q * DM + 8 * j); y1 += __ldcg(yp + q * DM + 8 * j + 1); }
          y0 = rbf(rbf(y0) * gate); y1 = rbf(rbf(y1) * gate);
          if (sel == row0) nr[2 * j] = pack_bf16(bf_lo(nr[2 * j]) + y0, bf_hi(nr[2 * j]) + y1);
          else nr[2 * j + 1] = pack_bf16(bf_lo(nr[2 * j + 1]) + y0, bf_hi(nr[2 * j + 1]) + y1);
        }
      }
      uint4 v[11];
      for (int n = 0; n < SPIN_LIMIT; n++) {
        bool ok = true;
#pragma unroll
        for (int i = 0; i < 11; i++) v[i] = ld_tagged(theirs + i * 128);
#pragma unroll
        for (int i = 0; i < 11; i++) ok &= v[i].w == ep;
        if (__all_sync(~0u, ok)) break;
      }
      TL(C.w * 16 + 10);
#pragma unroll
      for (int i = 0; i < 11; i++) {
        acc[3 * i] += __uint_as_float(v[i].x); acc[3 * i + 1] += __uint_as_float(v[i].y);
        if (i < 10) acc[3 * i + 2] += __uint_as_float(v[i].z);
      }
      uint32_t o[16];
#pragma unroll
      for (int i = 0; i < 16; i++)
        o[i] = pack_bf16(rbf(bf_lo(xr[i]) + rbf(acc[2 * i])) + bf_lo(nr[i]), rbf(bf_hi(xr[i]) + rbf(acc[2 * i + 1])) + bf_hi(nr[i]));
#pragma unroll
      for (int jj = 0; jj < 4; jj++) stsm4(xa + C.frag(jj, 0), o[4 * jj], o[4 * jj + 1], o[4 * jj + 2], o[4 * jj + 3]);
      __syncwarp();
#pragma unroll
      for (int i = 0; i < 4; i++) {
        const int row = 16 * wi + 4 * i + (lane >> 3);
        uint4 y;
        asm volatile("ld.shared.v4.u32 {%0, %1, %2, %3}, [%4];" : "=r"(y.x), "=r"(y.y), "=r"(y.z), "=r"(y.w) : "r"(xa + row * 128 + (((lane ^ row) & 7) << 4)) : "memory");
        *(uint4*)(P.out + (size_t)(j3 * 128 + 64 * C.w + row) * DM + ncol * 128 + 64 * ks + (lane & 7) * 8) = y;
      }
      TL(C.w * 16 + 11);
    }
  }
}

typedef CUresult (*EncodeFn)(CUtensorMap*, CUtensorMapDataType, cuuint32_t, void*, const cuuint64_t*, const cuuint64_t*,
                             const cuuint32_t*, const cuuint32_t*, CUtensorMapInterleave, CUtensorMapSwizzle,
                             CUtensorMapL2promotion, CUtensorMapFloatOOBfill);

void make_map(EncodeFn fn, CUtensorMap* m, const void* ptr, uint64_t cols, uint64_t rows, uint32_t box_rows) {
  cuuint64_t dims[2] = {cols, rows};
  cuuint64_t strides[1] = {cols * 2};
  cuuint32_t box[2] = {64, box_rows};
  cuuint32_t es[2] = {1, 1};
  fn(m, CU_TENSOR_MAP_DATA_TYPE_BFLOAT16, 2, const_cast<void*>(ptr), dims, strides, box, es, CU_TENSOR_MAP_INTERLEAVE_NONE,
     CU_TENSOR_MAP_SWIZZLE_128B, CU_TENSOR_MAP_L2_PROMOTION_L2_128B, CU_TENSOR_MAP_FLOAT_OOB_FILL_NONE);
}

}

extern "C" void kernel_launch(void* const* d_in, const int* in_sizes, int n_in, void* d_out, int out_size) {
  static EncodeFn fn = nullptr;
  static void* xn_ptr = nullptr;
  if (!fn) {
    void* f = nullptr;
    cudaDriverEntryPointQueryResult qr;
    cudaGetDriverEntryPoint("cuTensorMapEncodeTiled", &f, cudaEnableDefault, &qr);
    fn = (EncodeFn)f;
    cudaGetSymbolAddress(&xn_ptr, g_xn);
    cudaFuncSetAttribute(fused_kernel, cudaFuncAttributeMaxDynamicSharedMemorySize, SMEM_TOTAL);
  }
  Params P;
  make_map(fn, &P.x, d_in[0], DM, SEQ, 128);
  make_map(fn, &P.ckv, d_in[1], DM, SEQ, 128);
  make_map(fn, &P.xn, xn_ptr, DM, SEQ, 128);
  make_map(fn, &P.wq, d_in[2], NH * 128, DM, 128);
  make_map(fn, &P.wuk, d_in[3], NH * 128, DM, 128);
  make_map(fn, &P.wuv, d_in[4], NH * 128, DM, 128);
  make_map(fn, &P.wo, d_in[5], DM, NH * 128, 128);
  P.out = (__nv_bfloat16*)d_out;
  P.pwo = (const __nv_bfloat16*)d_in[5];
  P.neg = -1.f;
  P.zero = 0;
  P.px = (const __nv_bfloat16*)d_in[0];
  P.w_r = (const __nv_bfloat16*)d_in[7];
  P.w_gate = (const __nv_bfloat16*)d_in[8];
  P.w_up = (const __nv_bfloat16*)d_in[9];
  P.w_down = (const __nv_bfloat16*)d_in[10];
  fused_kernel<<<NCTA, 384, SMEM_TOTAL>>>(P);
}
```

```cpp
#include <cuda_runtime.h>
#include <cuda_bf16.h>
#include <cuda.h>
#include <stdint.h>

namespace {

constexpr int SEQ = 2048, DM = 512, NH = 32, FF = 1376;
constexpr int NSLOT = 6;
constexpr int TILE = 32768;
constexpr int HALF = 16384;
constexpr int SMEM_STG = NSLOT * TILE;
constexpr int SMEM_BAR = SMEM_STG + 32768;
constexpr int SMEM_TOTAL = SMEM_BAR + 256 + 1024;
constexpr int NCTA = 132;
constexpr int SPIN_LIMIT = 1 << 22;

constexpr int F_LN = 0;
constexpr int F_GRP = 16;
constexpr int F_CTX = 40;
constexpr int F_FFN = 104;
constexpr int F_MOE = 105;
constexpr int F_COUNT = 106;

__device__ __align__(1024) __nv_bfloat16 g_xn[SEQ * DM];
__device__ float g_r[SEQ];
__device__ __align__(1024) uint8_t g_qkv[3ull * NH * 16 * TILE];
__device__ __align__(1024) uint4 g_part[128 * 2 * 8 * 128];
__device__ float g_ypart[4 * DM];
__device__ unsigned g_flags[F_COUNT * 32];
__device__ unsigned g_epoch[NCTA];
#define TL(i)
#define TLX(i)
#define TR()

__device__ __forceinline__ uint32_t smem_u32(const void* p) { return (uint32_t)__cvta_generic_to_shared(p); }
__device__ __forceinline__ void mbar_init(uint32_t bar, int cnt) { asm volatile("mbarrier.init.shared::cta.b64 [%0], %1;" :: "r"(bar), "r"(cnt)); }
__device__ __forceinline__ void mbar_arrive(uint32_t bar) { asm volatile("mbarrier.arrive.shared::cta.b64 _, [%0];" :: "r"(bar) : "memory"); }
__device__ __forceinline__ void mbar_arrive_cluster_if(uint32_t bar, bool pred) {
  asm volatile("{\n.reg .pred p;\nsetp.ne.b32 p, %1, 0;\n@p mbarrier.arrive.shared::cluster.b64 _, [%0];\n}" :: "r"(bar), "r"((int)pred) : "memory");
}
__device__ __forceinline__ void mbar_expect(uint32_t bar, int bytes) { asm volatile("mbarrier.arrive.expect_tx.shared::cta.b64 _, [%0], %1;" :: "r"(bar), "r"(bytes) : "memory"); }
__device__ __forceinline__ void mbar_wait(uint32_t bar, uint32_t parity) {
  asm volatile("{\n.reg .pred p, q;\n.reg .b32 n;\n"
               "mbarrier.try_wait.parity.shared::cta.b64 p, [%0], %1;\n@p bra DONE;\nmov.b32 n, 0;\n"
               "LOOP:\nmbarrier.try_wait.parity.shared::cta.b64 p, [%0], %1;\nadd.s32 n, n, 1;\nsetp.lt.s32 q, n, %2;\n@p bra DONE;\n@q bra LOOP;\n"
               "DONE:\n}" :: "r"(bar), "r"(parity), "n"(SPIN_LIMIT) : "memory");
}
__device__ __forceinline__ void bulk_load(uint32_t dst, const void* src, int bytes, uint32_t bar) {
  asm volatile("cp.async.bulk.shared::cluster.global.mbarrier::complete_tx::bytes [%0], [%1], %2, [%3];" :: "r"(dst), "l"(src), "r"(bytes), "r"(bar) : "memory");
}
__device__ __forceinline__ void bulk_load_mc(uint32_t dst, const void* src, int bytes, uint32_t bar) {
  asm volatile("cp.async.bulk.shared::cluster.global.mbarrier::complete_tx::bytes.multicast::cluster [%0], [%1], %2, [%3], %4;" :: "r"(dst), "l"(src), "r"(bytes), "r"(bar), "h"((uint16_t)3) : "memory");
}
__device__ __forceinline__ void tma_load(uint32_t dst, const CUtensorMap* map, int c0, int c1, uint32_t bar) {
  asm volatile("cp.async.bulk.tensor.2d.shared::cluster.global.mbarrier::complete_tx::bytes [%0], [%1, {%3, %4}], [%2];" :: "r"(dst), "l"(map), "r"(bar), "r"(c0), "r"(c1) : "memory");
}
__device__ __forceinline__ void tma_load_mc(uint32_t dst, const CUtensorMap* map, int c0, int c1, uint32_t bar) {
  asm volatile("cp.async.bulk.tensor.2d.shared::cluster.global.mbarrier::complete_tx::bytes.multicast::cluster [%0], [%1, {%3, %4}], [%2], %5;" :: "r"(dst), "l"(map), "r"(bar), "r"(c0), "r"(c1), "h"((uint16_t)3) : "memory");
}
__device__ __forceinline__ void bulk_store(void* dst, uint32_t src, int bytes) {
  asm volatile("cp.async.bulk.global.shared::cta.bulk_group [%0], [%1], %2;" :: "l"(dst), "r"(src), "r"(bytes) : "memory");
}
__device__ __forceinline__ void st_tagged(uint4* p, uint32_t a, float b, float c, float d) {
  asm volatile("{\n.reg .b128 v;\n.reg .b64 lo, hi;\nmov.b64 lo, {%1, %2};\nmov.b64 hi, {%3, %4};\nmov.b128 v, {lo, hi};\n"
               "st.relaxed.gpu.global.b128 [%0], v;\n}" :: "l"(p), "r"(a), "r"(__float_as_uint(b)), "r"(__float_as_uint(c)), "r"(__float_as_uint(d)) : "memory");
}
__device__ __forceinline__ uint4 ld_tagged(const uint4* p) {
  uint4 r;
  asm volatile("{\n.reg .b128 v;\n.reg .b64 lo, hi;\nld.relaxed.gpu.global.b128 v, [%4];\nmov.b128 {lo, hi}, v;\n"
               "mov.b64 {%0, %1}, lo;\nmov.b64 {%2, %3}, hi;\n}" : "=r"(r.x), "=r"(r.y), "=r"(r.z), "=r"(r.w) : "l"(p) : "memory");
  return r;
}
__device__ __forceinline__ void l2_prefetch(const void* p, int bytes) { asm volatile("cp.async.bulk.prefetch.L2.global [%0], %1;" :: "l"(p), "r"(bytes) : "memory"); }
__device__ __forceinline__ void fence_async_smem() { asm volatile("fence.proxy.async.shared::cta;" ::: "memory"); }
__device__ __forceinline__ void fence_async_all() { asm volatile("fence.proxy.async;" ::: "memory"); }
__device__ __forceinline__ void flag_add(int f) { asm volatile("red.release.gpu.global.add.u32 [%0], 1;" :: "l"(&g_flags[f * 32]) : "memory"); }
__device__ __forceinline__ void flag_wait(int f, unsigned target) {
  const unsigned* p = &g_flags[f * 32];
  for (int n = 0; n < SPIN_LIMIT; ++n) {
    unsigned v;
    asm volatile("ld.acquire.gpu.global.u32 %0, [%1];" : "=r"(v) : "l"(p) : "memory");
    if ((int)(v - target) >= 0) break;
  }
}
__device__ __forceinline__ void bar_sync(int id, int n) { asm volatile("bar.sync %0, %1;" :: "r"(id), "r"(n) : "memory"); }
__device__ __forceinline__ void bar_arrive(int id, int n) { asm volatile("bar.arrive %0, %1;" :: "r"(id), "r"(n) : "memory"); }
__device__ __forceinline__ void wg_fence() { asm volatile("wgmma.fence.sync.aligned;" ::: "memory"); }
__device__ __forceinline__ void wg_commit() { asm volatile("wgmma.commit_group.sync.aligned;" ::: "memory"); }
template <int N> __device__ __forceinline__ void wg_wait() { asm volatile("wgmma.wait_group.sync.aligned %0;" :: "n"(N) : "memory"); }
template <int N> __device__ __forceinline__ void reg_fence(float (&d)[N]) {
#pragma unroll
  for (int i = 0; i < N; i++) asm volatile("" : "+f"(d[i]) :: "memory");
}
__device__ __forceinline__ void ldsm4(uint32_t addr, uint32_t& r0, uint32_t& r1, uint32_t& r2, uint32_t& r3) {
  asm volatile("ldmatrix.sync.aligned.m8n8.x4.shared.b16 {%0, %1, %2, %3}, [%4];" : "=r"(r0), "=r"(r1), "=r"(r2), "=r"(r3) : "r"(addr) : "memory");
}
__device__ __forceinline__ void stsm4(uint32_t addr, uint32_t r0, uint32_t r1, uint32_t r2, uint32_t r3) {
  asm volatile("stmatrix.sync.aligned.m8n8.x4.shared.b16 [%0], {%1, %2, %3, %4};" :: "r"(addr), "r"(r0), "r"(r1), "r"(r2), "r"(r3) : "memory");
}
__device__ __forceinline__ uint32_t pack_bf16(float lo, float hi) {
  uint32_t r; asm("cvt.rn.bf16x2.f32 %0, %1, %2;" : "=r"(r) : "f"(hi), "f"(lo)); return r;
}
__device__ __forceinline__ float ex2(float x) { float y; asm("ex2.approx.ftz.f32 %0, %1;" : "=f"(y) : "f"(x)); return y; }
__device__ __forceinline__ float bf_lo(uint32_t v) { return __uint_as_float(v << 16); }
__device__ __forceinline__ float bf_hi(uint32_t v) { return __uint_as_float(v & 0xffff0000u); }
__device__ __forceinline__ uint32_t add_bf16x2(uint32_t a, uint32_t b) { uint32_t r; asm("add.rn.bf16x2 %0, %1, %2;" : "=r"(r) : "r"(a), "r"(b)); return r; }
__device__ __forceinline__ float rbf(float x) { return __bfloat162float(__float2bfloat16_rn(x)); }

__device__ __forceinline__ uint32_t desc_lo(uint32_t addr) { return ((addr & 0x3FFFF) >> 4) | ((uint32_t)(HALF >> 4) << 16); }
__device__ __forceinline__ uint64_t desc(uint32_t lo) { return (uint64_t)lo | ((uint64_t)(64u | (1u << 30)) << 32); }

template<int TB> __device__ __forceinline__ void wgmma_ss_n128(float (&d)[64], uint64_t descA, uint64_t descB, int scaleD) {
  asm volatile("{\n.reg .pred p;\nsetp.ne.b32 p, %66, 0;\n"
    "wgmma.mma_async.sync.aligned.m64n128k16.f32.bf16.bf16 "
    "{%0, %1, %2, %3, %4, %5, %6, %7, %8, %9, %10, %11, %12, %13, %14, %15, "
    "%16, %17, %18, %19, %20, %21, %22, %23, %24, %25, %26, %27, %28, %29, %30, %31, "
    "%32, %33, %34, %35, %36, %37, %38, %39, %40, %41, %42, %43, %44, %45, %46, %47, "
    "%48, %49, %50, %51, %52, %53, %54, %55, %56, %57, %58, %59, %60, %61, %62, %63}, "
    "%64, %65, p, 1, 1, 0, %67;\n}\n"
    : "+f"(d[0]), "+f"(d[1]), "+f"(d[2]), "+f"(d[3]), "+f"(d[4]), "+f"(d[5]), "+f"(d[6]), "+f"(d[7]),
      "+f"(d[8]), "+f"(d[9]), "+f"(d[10]), "+f"(d[11]), "+f"(d[12]), "+f"(d[13]), "+f"(d[14]), "+f"(d[15]),
      "+f"(d[16]), "+f"(d[17]), "+f"(d[18]), "+f"(d[19]), "+f"(d[20]), "+f"(d[21]), "+f"(d[22]), "+f"(d[23]),
      "+f"(d[24]), "+f"(d[25]), "+f"(d[26]), "+f"(d[27]), "+f"(d[28]), "+f"(d[29]), "+f"(d[30]), "+f"(d[31]),
      "+f"(d[32]), "+f"(d[33]), "+f"(d[34]), "+f"(d[35]), "+f"(d[36]), "+f"(d[37]), "+f"(d[38]), "+f"(d[39]),
      "+f"(d[40]), "+f"(d[41]), "+f"(d[42]), "+f"(d[43]), "+f"(d[44]), "+f"(d[45]), "+f"(d[46]), "+f"(d[47]),
      "+f"(d[48]), "+f"(d[49]), "+f"(d[50]), "+f"(d[51]), "+f"(d[52]), "+f"(d[53]), "+f"(d[54]), "+f"(d[55]),
      "+f"(d[56]), "+f"(d[57]), "+f"(d[58]), "+f"(d[59]), "+f"(d[60]), "+f"(d[61]), "+f"(d[62]), "+f"(d[63])
    : "l"(descA), "l"(descB), "r"(scaleD), "n"(TB));
}

template<int TB> __device__ __forceinline__ void wgmma_rs_n128(float (&d)[64], uint32_t a0, uint32_t a1, uint32_t a2, uint32_t a3, uint64_t descB, int scaleD) {
  asm volatile("{\n.reg .pred p;\nsetp.ne.b32 p, %69, 0;\n"
    "wgmma.mma_async.sync.aligned.m64n128k16.f32.bf16.bf16 "
    "{%0, %1, %2, %3, %4, %5, %6, %7, %8, %9, %10, %11, %12, %13, %14, %15, "
    "%16, %17, %18, %19, %20, %21, %22, %23, %24, %25, %26, %27, %28, %29, %30, %31, "
    "%32, %33, %34, %35, %36, %37, %38, %39, %40, %41, %42, %43, %44, %45, %46, %47, "
    "%48, %49, %50, %51, %52, %53, %54, %55, %56, %57, %58, %59, %60, %61, %62, %63}, "
    "{%64, %65, %66, %67}, %68, p, 1, 1, %70;\n}\n"
    : "+f"(d[0]), "+f"(d[1]), "+f"(d[2]), "+f"(d[3]), "+f"(d[4]), "+f"(d[5]), "+f"(d[6]), "+f"(d[7]),
      "+f"(d[8]), "+f"(d[9]), "+f"(d[10]), "+f"(d[11]), "+f"(d[12]), "+f"(d[13]), "+f"(d[14]), "+f"(d[15]),
      "+f"(d[16]), "+f"(d[17]), "+f"(d[18]), "+f"(d[19]), "+f"(d[20]), "+f"(d[21]), "+f"(d[22]), "+f"(d[23]),
      "+f"(d[24]), "+f"(d[25]), "+f"(d[26]), "+f"(d[27]), "+f"(d[28]), "+f"(d[29]), "+f"(d[30]), "+f"(d[31]),
      "+f"(d[32]), "+f"(d[33]), "+f"(d[34]), "+f"(d[35]), "+f"(d[36]), "+f"(d[37]), "+f"(d[38]), "+f"(d[39]),
      "+f"(d[40]), "+f"(d[41]), "+f"(d[42]), "+f"(d[43]), "+f"(d[44]), "+f"(d[45]), "+f"(d[46]), "+f"(d[47]),
      "+f"(d[48]), "+f"(d[49]), "+f"(d[50]), "+f"(d[51]), "+f"(d[52]), "+f"(d[53]), "+f"(d[54]), "+f"(d[55]),
      "+f"(d[56]), "+f"(d[57]), "+f"(d[58]), "+f"(d[59]), "+f"(d[60]), "+f"(d[61]), "+f"(d[62]), "+f"(d[63])
    : "r"(a0), "r"(a1), "r"(a2), "r"(a3), "l"(descB), "r"(scaleD), "n"(TB));
}

template<int TB> __device__ __forceinline__ void wgmma_rs_n64(float (&d)[64], uint32_t a0, uint32_t a1, uint32_t a2, uint32_t a3, uint64_t descB, int scaleD) {
  asm volatile("{\n.reg .pred p;\nsetp.ne.b32 p, %37, 0;\n"
    "wgmma.mma_async.sync.aligned.m64n64k16.f32.bf16.bf16 "
    "{%0, %1, %2, %3, %4, %5, %6, %7, %8, %9, %10, %11, %12, %13, %14, %15, "
    "%16, %17, %18, %19, %20, %21, %22, %23, %24, %25, %26, %27, %28, %29, %30, %31}, "
    "{%32, %33, %34, %35}, %36, p, 1, 1, %38;\n}\n"
    : "+f"(d[0]), "+f"(d[1]), "+f"(d[2]), "+f"(d[3]), "+f"(d[4]), "+f"(d[5]), "+f"(d[6]), "+f"(d[7]),
      "+f"(d[8]), "+f"(d[9]), "+f"(d[10]), "+f"(d[11]), "+f"(d[12]), "+f"(d[13]), "+f"(d[14]), "+f"(d[15]),
      "+f"(d[16]), "+f"(d[17]), "+f"(d[18]), "+f"(d[19]), "+f"(d[20]), "+f"(d[21]), "+f"(d[22]), "+f"(d[23]),
      "+f"(d[24]), "+f"(d[25]), "+f"(d[26]), "+f"(d[27]), "+f"(d[28]), "+f"(d[29]), "+f"(d[30]), "+f"(d[31])
    : "r"(a0), "r"(a1), "r"(a2), "r"(a3), "l"(descB), "r"(scaleD), "n"(TB));
}

struct Cur {
  uint32_t o, phase;
  __device__ __forceinline__ void adv() { o += 8; if (o == 8 * NSLOT) { o = 0; phase ^= 1; } }
};

struct Params {
  CUtensorMap ckv, xn, x, wq, wuk, wuv, wo;
  __nv_bfloat16* out;
  const __nv_bfloat16 *pwo, *px, *w_r, *w_gate, *w_up, *w_down;
  float neg;
  uint32_t zero;
};

__device__ __forceinline__ void moe_cta(const Params& P, int q, unsigned ep, uint8_t* smem) {
  float* xs = (float*)smem;
  float* red = xs + DM;
  float* hs = red + 2 * 8 * 344;
  float* sv = hs + 344; int* si = (int*)(sv + 16);
  const int tid = threadIdx.x, lane = tid & 31, warp = tid >> 5;
  if (tid < 16) flag_wait(F_LN + tid, ep * 8);
  __syncthreads();
  float bv = -INFINITY; int bi = 0x7fffffff;
  for (int i = tid; i < SEQ; i += 384) { float v = __ldcg(&g_r[i]); if (v > bv || bi == 0x7fffffff) { bv = v; bi = i; } }
#pragma unroll
  for (int o = 16; o; o >>= 1) {
    float ov = __shfl_xor_sync(~0u, bv, o); int oi = __shfl_xor_sync(~0u, bi, o);
    if (ov > bv || (ov == bv && oi < bi)) { bv = ov; bi = oi; }
  }
  if (lane == 0) { sv[warp] = bv; si[warp] = bi; }
  __syncthreads();
  bv = sv[0]; bi = si[0];
  for (int w = 1; w < 12; w++) { float ov = sv[w]; int oi = si[w]; if (ov > bv || (ov == bv && oi < bi)) { bv = ov; bi = oi; } }
  for (int i = tid; i < DM; i += 384) xs[i] = __bfloat162float(__ldcg(&g_xn[bi * DM + i]));
  __syncthreads();
  const int f0 = q * 344;
  if (tid < 344) {
    const int cg = tid % 43, ksl = tid / 43;
    float ag[8], au[8];
#pragma unroll
    for (int i = 0; i < 8; i++) ag[i] = au[i] = 0.f;
    const __nv_bfloat16* pg = P.w_gate + (size_t)(ksl * 64) * FF + f0 + cg * 8;
    const __nv_bfloat16* pu = P.w_up + (size_t)(ksl * 64) * FF + f0 + cg * 8;
#pragma unroll 8
    for (int k = 0; k < 64; k++) {
      uint4 a = __ldg((const uint4*)(pg + (size_t)k * FF)), b = __ldg((const uint4*)(pu + (size_t)k * FF));
      float xv = xs[ksl * 64 + k];
      ag[0] += xv * bf_lo(a.x); ag[1] += xv * bf_hi(a.x); ag[2] += xv * bf_lo(a.y); ag[3] += xv * bf_hi(a.y);
      ag[4] += xv * bf_lo(a.z); ag[5] += xv * bf_hi(a.z); ag[6] += xv * bf_lo(a.w); ag[7] += xv * bf_hi(a.w);
      au[0] += xv * bf_lo(b.x); au[1] += xv * bf_hi(b.x); au[2] += xv * bf_lo(b.y); au[3] += xv * bf_hi(b.y);
      au[4] += xv * bf_lo(b.z); au[5] += xv * bf_hi(b.z); au[6] += xv * bf_lo(b.w); au[7] += xv * bf_hi(b.w);
    }
#pragma unroll
    for (int i = 0; i < 8; i++) { red[ksl * 344 + cg * 8 + i] = ag[i]; red[(8 + ksl) * 344 + cg * 8 + i] = au[i]; }
  }
  __syncthreads();
  if (tid < 344) {
    float g = 0.f, u = 0.f;
#pragma unroll
    for (int i = 0; i < 8; i++) { g += red[i * 344 + tid]; u += red[(8 + i) * 344 + tid]; }
    g = rbf(g); u = rbf(u);
    g = rbf(g / (1.f + expf(-g)));
    hs[tid] = rbf(g * u);
  }
  __syncthreads();
  {
    const int cg = tid & 63, fs = tid >> 6;
    float ay[8];
#pragma unroll
    for (int i = 0; i < 8; i++) ay[i] = 0.f;
    const __nv_bfloat16* pd = P.w_down + (size_t)f0 * DM + cg * 8;
#pragma unroll 8
    for (int f = fs; f < 344; f += 6) {
      uint4 a = __ldg((const uint4*)(pd + (size_t)f * DM));
      float hv = hs[f];
      ay[0] += hv * bf_lo(a.x); ay[1] += hv * bf_hi(a.x); ay[2] += hv * bf_lo(a.y); ay[3] += hv * bf_hi(a.y);
      ay[4] += hv * bf_lo(a.z); ay[5] += hv * bf_hi(a.z); ay[6] += hv * bf_lo(a.w); ay[7] += hv * bf_hi(a.w);
    }
#pragma unroll
    for (int i = 0; i < 8; i++) red[fs * DM + cg * 8 + i] = ay[i];
  }
  __syncthreads();
  for (int i = tid; i < DM; i += 384) {
    float y = 0.f;
#pragma unroll
    for (int s = 0; s < 6; s++) y += red[s * DM + i];
    g_ypart[q * DM + i] = y;
  }
  __syncthreads();
  if (tid == 0) { __threadfence(); flag_add(F_FFN); }
  if (q == 0) {
    if (tid < 8) flag_wait(F_GRP + 3 * tid + 1, ep * 32);
    if (tid == 8) flag_wait(F_FFN, ep * 4);
    __syncthreads();
    const float gate = rbf(1.f / (1.f + expf(-bv)));
    for (int i = tid; i < DM; i += 384) {
      const float y = (__ldcg(&g_ypart[i]) + __ldcg(&g_ypart[DM + i])) + (__ldcg(&g_ypart[2 * DM + i]) + __ldcg(&g_ypart[3 * DM + i]));
      g_xn[bi * DM + i] = __float2bfloat16_rn(xs[i] + rbf(rbf(y) * gate));
    }
    __syncthreads();
    if (tid == 0) { __threadfence(); fence_async_all(); flag_add(F_MOE); }
  }
}

__device__ __forceinline__ float half_sum(float v) {
#pragma unroll
  for (int o = 8; o; o >>= 1) v += __shfl_xor_sync(~0u, v, o);
  return v;
}
__device__ __forceinline__ void ln_row(const Params& P, int row, int l16, const uint4 (&xi)[4], const uint4 (&wi)[4]) {
  uint32_t x[16], w[16];
#pragma unroll
  for (int i = 0; i < 4; i++) {
    x[4 * i] = xi[i].x; x[4 * i + 1] = xi[i].y; x[4 * i + 2] = xi[i].z; x[4 * i + 3] = xi[i].w;
    w[4 * i] = wi[i].x; w[4 * i + 1] = wi[i].y; w[4 * i + 2] = wi[i].z; w[4 * i + 3] = wi[i].w;
  }
  float s[4] = {0.f, 0.f, 0.f, 0.f};
#pragma unroll
  for (int k = 0; k < 16; k++) { s[k & 1] += bf_lo(x[k]); s[2 + (k & 1)] += bf_hi(x[k]); }
  const float mean = half_sum((s[0] + s[1]) + (s[2] + s[3])) * (1.f / DM);
  s[0] = s[1] = s[2] = s[3] = 0.f;
#pragma unroll
  for (int k = 0; k < 16; k++) {
    const float d0 = bf_lo(x[k]) - mean, d1 = bf_hi(x[k]) - mean;
    s[k & 1] = fmaf(d0, d0, s[k & 1]); s[2 + (k & 1)] = fmaf(d1, d1, s[2 + (k & 1)]);
  }
  const float var = half_sum((s[0] + s[1]) + (s[2] + s[3])) * (1.f / DM);
  const uint32_t mb = pack_bf16(mean, mean);
  const float rs = __frcp_rn(rbf(__fsqrt_rn(rbf(rbf(var) + 1e-5f))));
  s[0] = s[1] = s[2] = s[3] = 0.f;
#pragma unroll
  for (int k = 0; k < 16; k++) {
    uint32_t d;
    asm("sub.rn.bf16x2 %0, %1, %2;" : "=r"(d) : "r"(x[k]), "r"(mb));
    x[k] = pack_bf16(bf_lo(d) * rs, bf_hi(d) * rs);
    s[k & 1] = fmaf(bf_lo(x[k]), bf_lo(w[k]), s[k & 1]); s[2 + (k & 1)] = fmaf(bf_hi(x[k]), bf_hi(w[k]), s[2 + (k & 1)]);
  }
  uint4* dst = (uint4*)(g_xn + (size_t)row * DM) + l16;
#pragma unroll
  for (int i = 0; i < 4; i++) dst[16 * i] = make_uint4(x[4 * i], x[4 * i + 1], x[4 * i + 2], x[4 * i + 3]);
  const float r = half_sum((s[0] + s[1]) + (s[2] + s[3]));
  if (l16 == 0) g_r[row] = rbf(r);
}

struct Ctx {
  uint32_t sb;
  uint32_t dlo;
  uint32_t full0;
  uint32_t rel;
  bool rel_pred, warp0;
  uint32_t stg;
  uint32_t stg_full, stg_empty;
  uint32_t stg_phase;
  uint32_t frag_off;
  uint32_t frag_x;
  int w;
  float neg;
  uint32_t zero;
  __device__ __forceinline__ void wait(const Cur& c) const { mbar_wait(full0 + c.o, c.phase); }
  __device__ __forceinline__ void release(const Cur& c) const { mbar_arrive_cluster_if(rel + c.o, rel_pred); }
  __device__ __forceinline__ void skip(const Cur& c) const { if (warp0) { wait(c); release(c); } }
  __device__ __forceinline__ uint32_t addr(const Cur& c) const { return sb + c.o * (TILE / 8); }
  __device__ __forceinline__ uint32_t dsc(const Cur& c) const { return dlo + c.o * (TILE / 128); }
  int trn;
  __device__ __forceinline__ void turn_begin() { bar_sync(1 + w, 256); }
  __device__ __forceinline__ void turn_end() { bar_arrive(2 - w, 256); TR(); }
  __device__ __forceinline__ uint32_t frag(int jj, int hstride) const { return (jj >> 2) * hstride + frag_off + (((jj & 3) * 32) ^ frag_x); }
  __device__ __forceinline__ void stage_acquire() { mbar_wait(stg_empty, stg_phase ^ 1); stg_phase ^= 1; }
  template <bool SCALE> __device__ __forceinline__ void stage_out(const float (&d)[64], float s0, float s1) {
#pragma unroll
    for (int jj = 0; jj < 8; jj++) {
      if (SCALE)
        stsm4(stg + frag(jj, 8192), pack_bf16(d[8 * jj] * s0, d[8 * jj + 1] * s0), pack_bf16(d[8 * jj + 2] * s1, d[8 * jj + 3] * s1),
              pack_bf16(d[8 * jj + 4] * s0, d[8 * jj + 5] * s0), pack_bf16(d[8 * jj + 6] * s1, d[8 * jj + 7] * s1));
      else
        stsm4(stg + frag(jj, 8192), pack_bf16(d[8 * jj], d[8 * jj + 1]), pack_bf16(d[8 * jj + 2], d[8 * jj + 3]),
              pack_bf16(d[8 * jj + 4], d[8 * jj + 5]), pack_bf16(d[8 * jj + 6], d[8 * jj + 7]));
    }
  }
  __device__ __forceinline__ void publish() const { fence_async_smem(); mbar_arrive(stg_full); }
};

constexpr float SM_SCALE = 0.08838834764831845f * 1.4426950408889634f;
constexpr float SUM_LIMIT = 1152921504606846976.f;

struct Attn {
  float o[64], s[64];
  uint32_t p[32], q[32];
  float n0, n1;
  float l0, l1;
};

__device__ __forceinline__ void issue_qk(Attn& A, uint32_t d) {
#pragma unroll
  for (int kk = 0; kk < 8; kk++)
    wgmma_rs_n128<0>(A.s, A.q[4 * kk], A.q[4 * kk + 1], A.q[4 * kk + 2], A.q[4 * kk + 3], desc(d + (((kk >> 2) * HALF + (kk & 3) * 32) >> 4)), kk > 0);
  wg_commit();
}
__device__ __forceinline__ void issue_qk_half(Attn& A, uint32_t d) {
#pragma unroll
  for (int kk = 0; kk < 8; kk++)
    wgmma_rs_n64<0>(A.s, A.q[4 * kk], A.q[4 * kk + 1], A.q[4 * kk + 2], A.q[4 * kk + 3], desc(d + (((kk >> 2) * HALF + (kk & 3) * 32) >> 4)), kk > 0);
  wg_commit();
}
template <int NK> __device__ __forceinline__ void issue_pv_n(Attn& A, uint32_t d, int acc) {
  wg_fence();
#pragma unroll
  for (int kk = 0; kk < NK; kk++)
    wgmma_rs_n128<1>(A.o, A.p[4 * kk], A.p[4 * kk + 1], A.p[4 * kk + 2], A.p[4 * kk + 3], desc(d + ((kk * 2048) >> 4)), kk > 0 ? 1 : acc);
  wg_commit();
}
__device__ __forceinline__ void issue_pv(Attn& A, uint32_t d, int acc, bool upper) {
  if (upper) issue_pv_n<8>(A, d, acc); else issue_pv_n<4>(A, d, acc);
}
template <int N> __device__ __forceinline__ void pack_p(Attn& A) {
#pragma unroll
  for (int i = 0; i < N; i++) A.p[i] = pack_bf16(A.s[2 * i], A.s[2 * i + 1]);
}
template <int NJ> __device__ __forceinline__ void block_max(const Attn& A, float& n0, float& n1) {
  float x0 = fmaxf(A.s[0], A.s[1]), x1 = fmaxf(A.s[2], A.s[3]);
  float y0 = fmaxf(A.s[4], A.s[5]), y1 = fmaxf(A.s[6], A.s[7]);
#pragma unroll
  for (int j = 2; j < NJ; j += 2) {
    x0 = fmaxf(x0, fmaxf(A.s[4 * j], A.s[4 * j + 1])); x1 = fmaxf(x1, fmaxf(A.s[4 * j + 2], A.s[4 * j + 3]));
    y0 = fmaxf(y0, fmaxf(A.s[4 * j + 4], A.s[4 * j + 5])); y1 = fmaxf(y1, fmaxf(A.s[4 * j + 6], A.s[4 * j + 7]));
  }
  x0 = fmaxf(x0, y0); x1 = fmaxf(x1, y1);
  x0 = fmaxf(x0, __shfl_xor_sync(~0u, x0, 1)); x1 = fmaxf(x1, __shfl_xor_sync(~0u, x1, 1));
  x0 = fmaxf(x0, __shfl_xor_sync(~0u, x0, 2)); x1 = fmaxf(x1, __shfl_xor_sync(~0u, x1, 2));
  n0 = -x0 * SM_SCALE; n1 = -x1 * SM_SCALE;
}
template <int J0, int J1> __device__ __forceinline__ void exp_cols(Attn& A, float (&a)[4]) {
#pragma unroll
  for (int j = J0; j < J1; j++) {
    A.s[4 * j] = ex2(fmaf(A.s[4 * j], SM_SCALE, A.n0)); A.s[4 * j + 1] = ex2(fmaf(A.s[4 * j + 1], SM_SCALE, A.n0));
    A.s[4 * j + 2] = ex2(fmaf(A.s[4 * j + 2], SM_SCALE, A.n1)); A.s[4 * j + 3] = ex2(fmaf(A.s[4 * j + 3], SM_SCALE, A.n1));
    if (j == 0) { a[0] = A.s[0]; a[1] = A.s[1]; a[2] = A.s[2]; a[3] = A.s[3]; }
    else { a[0] += A.s[4 * j]; a[1] += A.s[4 * j + 1]; a[2] += A.s[4 * j + 2]; a[3] += A.s[4 * j + 3]; }
  }
}
__device__ __forceinline__ void pin(float v, float neg, uint32_t addr) {
  asm volatile("{\n.reg .pred p;\nsetp.lt.f32 p, %0, %2;\n@p mbarrier.arrive.shared::cta.b64 _, [%1];\n}" :: "f"(v), "r"(addr), "f"(neg) : "memory");
}
__device__ __forceinline__ void causal_mask(Attn& A, int rel) {
#pragma unroll
  for (int j = 0; j < 16; j++) {
    if (8 * j > rel) A.s[4 * j] = -INFINITY;
    if (8 * j + 1 > rel) A.s[4 * j + 1] = -INFINITY;
    if (8 * j > rel + 8) A.s[4 * j + 2] = -INFINITY;
    if (8 * j + 1 > rel + 8) A.s[4 * j + 3] = -INFINITY;
  }
}
template <int G0> __device__ __forceinline__ void quad_mask(Attn& A, int wi) {
  const int lane = threadIdx.x & 31;
  const bool m0 = 2 * (lane & 3) > (lane >> 2), m1 = 2 * (lane & 3) + 1 > (lane >> 2);
#pragma unroll
  for (int jj = 0; jj < 4; jj++) {
    float* s = A.s + 8 * (G0 + jj);
    if (jj >= wi) {
      asm volatile("" ::: "memory");
      const bool all = jj > wi;
      s[4] = s[5] = -INFINITY;
      if (all) s[2] = s[3] = -INFINITY;
      if (all || m0) s[0] = s[6] = -INFINITY;
      if (all || m1) s[1] = s[7] = -INFINITY;
    }
  }
}
__device__ __forceinline__ void inv_sums(const Attn& A, float& r0, float& r1) {
  float l0 = A.l0, l1 = A.l1;
  l0 += __shfl_xor_sync(~0u, l0, 1); l1 += __shfl_xor_sync(~0u, l1, 1);
  l0 += __shfl_xor_sync(~0u, l0, 2); l1 += __shfl_xor_sync(~0u, l1, 2);
  r0 = __fdividef(1.f, l0); r1 = __fdividef(1.f, l1);
}
__device__ __forceinline__ void redo_block(Attn& A, const uint8_t* ktile, bool diag, int rel, uint32_t zero) {
  const int lane = threadIdx.x & 31;
  uint32_t off = (lane >> 2) * 144 + (lane & 3) * 4;
#pragma unroll
  for (int j = 0; j < 16; j++) {
    float c0 = 0.f, c1 = 0.f, c2 = 0.f, c3 = 0.f;
    if (j > 0) off += __float_as_uint(A.s[4 * j - 4]) & zero;
#pragma unroll
    for (int kk = 0; kk < 8; kk++) {
      const uint32_t b0 = __ldcg((const uint32_t*)(ktile + (off ^ ((kk & 3) * 32)) + j * 1024 + (kk >> 2) * HALF));
      const uint32_t b1 = __ldcg((const uint32_t*)(ktile + (off ^ ((kk & 3) * 32 + 16)) + j * 1024 + (kk >> 2) * HALF));
      asm volatile("mma.sync.aligned.m16n8k16.row.col.f32.bf16.bf16.f32 {%0, %1, %2, %3}, {%4, %5, %6, %7}, {%8, %9}, {%0, %1, %2, %3};"
                   : "+f"(c0), "+f"(c1), "+f"(c2), "+f"(c3)
                   : "r"(A.q[4 * kk]), "r"(A.q[4 * kk + 1]), "r"(A.q[4 * kk + 2]), "r"(A.q[4 * kk + 3]), "r"(b0), "r"(b1) : "memory");
    }
    A.s[4 * j] = c0; A.s[4 * j + 1] = c1; A.s[4 * j + 2] = c2; A.s[4 * j + 3] = c3;
  }
  if (diag) causal_mask(A, rel);
  float n0, n1, a[4];
  block_max<16>(A, n0, n1);
  n0 = fminf(n0, A.n0); n1 = fminf(n1, A.n1);
  const float c0 = ex2(n0 - A.n0), c1 = ex2(n1 - A.n1);
  A.n0 = n0; A.n1 = n1;
  exp_cols<0, 16>(A, a);
  A.l0 = fmaf(A.l0, c0, a[0] + a[1]); A.l1 = fmaf(A.l1, c1, a[2] + a[3]);
#pragma unroll
  for (int j = 0; j < 16; j++) { A.o[4 * j] *= c0; A.o[4 * j + 1] *= c0; A.o[4 * j + 2] *= c1; A.o[4 * j + 3] *= c1; }
  pack_p<32>(A);
}
__device__ __forceinline__ void round_first(Ctx& C, Attn& A, Cur& cur, bool diag, int rel) {
  const Cur ck = cur; cur.adv();
  C.wait(ck);
  C.turn_begin();
  wg_fence();
  issue_qk(A, C.dsc(ck));
  C.turn_end();
  wg_wait<0>();
  reg_fence(A.s);
  C.release(ck);
  if (diag) causal_mask(A, rel);
  block_max<16>(A, A.n0, A.n1);
  float a[4];
  exp_cols<0, 16>(A, a);
  A.l0 = a[0] + a[1]; A.l1 = a[2] + a[3];
  pack_p<32>(A);
}
__device__ __forceinline__ void round_begin(Ctx& C, Attn& A, Cur& cur, bool skip, int pv_acc, bool pub, bool diag, int rel, float (&a)[4]) {
  Cur cv;
  if (skip) { C.skip(cur); cur.adv(); cv = cur; cur.adv(); }
  const Cur cq = cur; cur.adv();
  const Cur ck = cur; cur.adv();
  const Cur cs = cur; cur.adv();
  if (!skip) cv = cs;
  C.wait(cq);
  const uint32_t qa = C.addr(cq) + C.w * 8192;
#pragma unroll
  for (int jj = 0; jj < 8; jj++) ldsm4(qa + C.frag(jj, HALF), A.q[4 * jj], A.q[4 * jj + 1], A.q[4 * jj + 2], A.q[4 * jj + 3]);
  C.wait(ck);
  C.turn_begin();
  C.release(cq);
  wg_fence();
  issue_qk(A, C.dsc(ck));
  C.wait(cv);
  issue_pv(A, C.dsc(cv), pv_acc, C.w);
  C.turn_end();
  if (pub) C.publish();
  C.stage_acquire();
  float r0, r1;
  inv_sums(A, r0, r1);
  A.l0 = A.l1 = 0.f;
  wg_wait<1>();
  reg_fence(A.s);
  C.release(ck);
  if (diag) causal_mask(A, rel);
  block_max<2>(A, A.n0, A.n1);
  exp_cols<0, 6>(A, a);
  pin((a[0] + a[1]) + (a[2] + a[3]), C.neg, C.stg_full);
  wg_wait<0>();
  reg_fence(A.o);
  C.release(cv);
  C.stage_out<true>(A.o, r0, r1);
  exp_cols<6, 16>(A, a);
  pack_p<32>(A);
  if (skip) C.skip(cs);
}
template <bool HALF_BLOCK> __device__ __forceinline__ void round_step(Ctx& C, Attn& A, Cur& cur, int pv_acc, bool pub, bool diag, int wi, float (&a)[4]) {
  const Cur ck = cur; cur.adv();
  const Cur cv = cur; cur.adv();
  C.wait(ck);
  C.turn_begin();
  wg_fence();
  if (HALF_BLOCK) issue_qk_half(A, C.dsc(ck)); else issue_qk(A, C.dsc(ck));
  C.wait(cv);
  issue_pv(A, C.dsc(cv), pv_acc, true);
  C.turn_end();
  if (pub) C.publish();
  wg_wait<1>();
  reg_fence(A.s);
  C.release(ck);
  if (HALF_BLOCK) quad_mask<0>(A, wi); else if (diag) quad_mask<4>(A, wi);
  exp_cols<0, 8>(A, a);
  pin((a[0] + a[1]) + (a[2] + a[3]), C.neg, C.stg_full);
  wg_wait<0>();
  reg_fence(A.o);
  C.release(cv);
  if (HALF_BLOCK) pack_p<16>(A);
  else { exp_cols<8, 16>(A, a); pack_p<32>(A); }
}

template <bool LOAD_A> __device__ __forceinline__ void proj_unit(Ctx& C, Cur& cur, uint32_t (&a)[128], float (&acc)[64], bool pub, bool acq) {
#pragma unroll
  for (int i = 0; i < 4; i++) {
    Cur ca = cur;
    if (LOAD_A) {
      cur.adv();
      C.wait(ca);
      const uint32_t aa = C.addr(ca) + C.w * 8192;
#pragma unroll
      for (int jj = 0; jj < 8; jj++) ldsm4(aa + C.frag(jj, HALF), a[32 * i + 4 * jj], a[32 * i + 4 * jj + 1], a[32 * i + 4 * jj + 2], a[32 * i + 4 * jj + 3]);
    }
    const Cur cb = cur; cur.adv();
    C.wait(cb);
    C.turn_begin();
    if (LOAD_A) C.release(ca);
    wg_fence();
    const uint32_t d = C.dsc(cb);
#pragma unroll
    for (int kk = 0; kk < 8; kk++)
      wgmma_rs_n128<1>(acc, a[32 * i + 4 * kk], a[32 * i + 4 * kk + 1], a[32 * i + 4 * kk + 2], a[32 * i + 4 * kk + 3], desc(d + ((kk * 2048) >> 4)), (i | kk) > 0);
    wg_commit();
    C.turn_end();
    if (i == 0 && pub) C.publish();
    if (i == 3 && acq) C.stage_acquire();
    wg_wait<0>();
    reg_fence(acc);
    C.release(cb);
  }
}

__global__ void __cluster_dims__(2, 1, 1) __launch_bounds__(384, 1) fused_kernel(const __grid_constant__ Params P) {
  extern __shared__ uint8_t smem_raw[];
  uint8_t* smem = smem_raw + ((1024 - (smem_u32(smem_raw) & 1023)) & 1023);
  const int tid = threadIdx.x;
  const int c = blockIdx.x >> 1, r = blockIdx.x & 1;
  const unsigned ep = g_epoch[blockIdx.x] + 1;
  if (c >= 64) {
    moe_cta(P, blockIdx.x - 128, ep, smem);
    if (tid == 0) g_epoch[blockIdx.x] = ep;
    return;
  }
  const int rp = c & 7, g = c >> 3;
  const int rb = 2 * rp + r;
  const int j3 = c & 15, ks = c >> 5, ncol = 2 * ((c >> 4) & 1) + r;
  const uint32_t sb = smem_u32(smem);
  const uint32_t full0 = sb + SMEM_BAR, empty0 = full0 + 8 * NSLOT, stgf0 = empty0 + 8 * NSLOT, stge0 = stgf0 + 16;
  if (tid == 0) {
    for (int i = 0; i < NSLOT; i++) { mbar_init(full0 + 8 * i, 1); mbar_init(empty0 + 8 * i, 4); }
    for (int i = 0; i < 2; i++) { mbar_init(stgf0 + 8 * i, 128); mbar_init(stge0 + 8 * i, 1); }
    asm volatile("fence.mbarrier_init.release.cluster;" ::: "memory");
  }
  __syncwarp();
  asm volatile("barrier.cluster.arrive.relaxed.aligned;" ::: "memory");
  if (tid == 0) {
    mbar_expect(full0, TILE);
    tma_load(sb, &P.ckv, 0, rb * 128, full0);
    tma_load(sb + HALF, &P.ckv, 64, rb * 128, full0);
    asm volatile("prefetch.tensormap [%0];" :: "l"(&P.wuk) : "memory");
  }
  const int ln_r = rb * 128 + 16 * g + ((tid >> 4) & 15);
  uint4 ln_x[4], ln_w[4];
#pragma unroll
  for (int i = 0; i < 4; i++) {
    ln_x[i] = __ldg((const uint4*)(P.px + (size_t)ln_r * DM) + 16 * i + (tid & 15));
    ln_w[i] = __ldg((const uint4*)P.w_r + 16 * i + (tid & 15));
  }
  __syncwarp();
  asm volatile("barrier.cluster.wait.aligned;" ::: "memory");
  const int wg = __shfl_sync(~0u, tid >> 7, 0);

  if (wg == 0) {
    asm volatile("setmaxnreg.dec.sync.aligned.u32 40;");
    const int warp = tid >> 5;
    if (warp == 0) {
      if (tid == 0) {
        Cur cur{8, 0};
        uint32_t dst, bar;
        auto acquire = [&]() {
          mbar_wait(empty0 + cur.o, cur.phase ^ 1);
          dst = sb + cur.o * (TILE / 8); bar = full0 + cur.o;
          mbar_expect(bar, TILE);
          cur.adv();
        };
        for (int u = 0; u < 12; u++) {
          const CUtensorMap* wm = u >= 8 ? &P.wq : ((u & 1) ? &P.wuv : &P.wuk);
          const CUtensorMap* am = u >= 8 ? &P.xn : &P.ckv;
          const int head = 4 * g + (u >= 8 ? (0x0231 >> (4 * (u - 8))) & 3 : 3 - (u >> 1));
          if (u == 4) { flag_wait(F_LN + rb, ep * 8); fence_async_all(); }
          if (u == 6) l2_prefetch(g_xn + (size_t)(rb * 128 + 16 * g) * DM, HALF);
          for (int i = 0; i < 4; i++) {
            if ((u & 7) == 0 && (u | i)) {
              acquire();
              tma_load(dst, am, 128 * i, rb * 128, bar);
              tma_load(dst + HALF, am, 128 * i + 64, rb * 128, bar);
            }
            acquire();
            tma_load_mc(dst + r * HALF, wm, head * 128 + 64 * r, 128 * i, bar);
          }
        }
        const uint8_t* prev_v = nullptr;
        for (int it = 0; it < 4; it++) {
          const int head = 4 * g + it;
          const int j = (it & 1) ? 15 - rb : rb;
          if (it < 3) { flag_wait(F_GRP + 3 * g + it, ep * 32); fence_async_all(); }
          else { l2_prefetch(P.pwo + (size_t)blockIdx.x * (TILE / 2), TILE); flag_wait(F_MOE, ep); }
          if (it > 0) {
            acquire();
            bulk_load(dst, g_qkv + (size_t)(head * 16 + j) * TILE, TILE, bar);
          }
          for (int b = 0; b <= (j | 1); b++) {
            acquire();
            bulk_load_mc(dst + r * HALF, g_qkv + (size_t)((NH + head) * 16 + b) * TILE + r * HALF, HALF, bar);
            if (prev_v) { acquire(); bulk_load_mc(dst + r * HALF, prev_v, HALF, bar); }
            prev_v = g_qkv + (size_t)((2 * NH + head) * 16 + b) * TILE + r * HALF;
          }
        }
        acquire(); bulk_load_mc(dst + r * HALF, prev_v, HALF, bar);
        for (int t = 0; t < 32; t++) {
          const int head = 16 * ks + 4 * ((t & 15) >> 2) + 2 * (t >> 4) + ((t >> 1) & 1);
          if ((t & 15) == 0) { flag_wait(F_CTX + j3 * 4 + ks * 2 + (t >> 4), ep * 16); fence_async_all(); }
          acquire();
          bulk_load_mc(dst + r * 8192, g_qkv + (size_t)(head * 16 + j3) * TILE + (t & 1) * HALF + r * 8192, 8192, bar);
          tma_load(dst + HALF + ks * 8192, &P.wo, ncol * 128, head * 128 + (t & 1) * 64, bar);
          tma_load(dst + HALF + (ks ^ 1) * 8192, &P.wo, ncol * 128 + 64, head * 128 + (t & 1) * 64, bar);
        }
        acquire();
        tma_load(dst, &P.x, ncol * 128 + 64 * ks, j3 * 128, bar);
        tma_load(dst + HALF, &P.xn, ncol * 128 + 64 * ks, j3 * 128, bar);
        for (int i = 0; i < NSLOT; i++) { mbar_wait(empty0 + cur.o, cur.phase ^ 1); cur.adv(); }
        g_epoch[blockIdx.x] = ep;
      }
    } else if (warp == 3) {
      bar_sync(3, 288);
      if (tid == 96) { __threadfence(); fence_async_all(); flag_add(F_LN + rb); }
    } else {
      if ((tid & 31) == 0) {
        const int w = warp - 1;
        const uint32_t stg = sb + SMEM_STG + w * HALF;
        for (int job = 0; job < 15; job++) {
          int tile, flag = -1;
          if (job < 8) {
            tile = ((1 + (job & 1)) * NH + 4 * g + 3 - (job >> 1)) * 16 + rb;
            if (job == 7) flag = F_GRP + 3 * g;
          } else if (job < 11) {
            tile = (4 * g + ((0x231 >> (4 * (job - 8))) & 3)) * 16 + rb;
            if (job != 9) flag = F_GRP + 3 * g + (job >> 1) - 3;
          } else {
            const int it = job - 11;
            const int j = (it & 1) ? 15 - rb : rb;
            tile = (4 * g + it) * 16 + j;
            flag = F_CTX + j * 4 + (g >> 2) * 2 + (it >> 1);
          }
          uint8_t* d = g_qkv + (size_t)tile * TILE + w * 8192;
          mbar_wait(stgf0 + 8 * w, job & 1);
          bulk_store(d, stg, 8192);
          bulk_store(d + HALF, stg + 8192, 8192);
          asm volatile("cp.async.bulk.commit_group;" ::: "memory");
          asm volatile("cp.async.bulk.wait_group.read 0;" ::: "memory");
          mbar_arrive(stge0 + 8 * w);
          if (flag >= 0) {
            asm volatile("cp.async.bulk.wait_group 0;" ::: "memory");
            fence_async_all();
            flag_add(flag);
          }
          if (w == 1 && (job == 8 || job == 10 || job >= 13)) TLX(job == 8 ? 28 : job == 10 ? 29 : 17 + job);
        }
      }
    }
  } else {
    asm volatile("setmaxnreg.inc.sync.aligned.u32 232;");
    const int t = tid & 127, lane = tid & 31, wi = t >> 5;
    Ctx C;
    C.trn = 0; C.neg = P.neg; C.zero = P.zero; C.sb = sb; C.dlo = desc_lo(sb); C.full0 = full0; C.w = wg - 1;
    asm("mapa.shared::cluster.u32 %0, %1, %2;" : "=r"(C.rel) : "r"(empty0), "r"(lane & 1));
    C.rel_pred = t < 2;
    const int wiu = __shfl_sync(~0u, wi, 0);
    C.warp0 = wiu == 0;
    C.stg = sb + SMEM_STG + C.w * HALF;
    C.stg_full = stgf0 + 8 * C.w; C.stg_empty = stge0 + 8 * C.w; C.stg_phase = 0;
    C.frag_off = (16 * wi + (lane & 15)) * 128;
    C.frag_x = ((lane >> 4) ^ (lane & 7)) * 16;
    TL(C.w * 16 + 0);
    ln_row(P, ln_r, tid & 15, ln_x, ln_w);
    bar_arrive(3, 288);
    if (C.w == 1) bar_arrive(1, 256);
    Cur cur{0, 0};
    Attn A;
    TL(C.w * 16 + 1);
    {
      uint32_t a[128];
      float acc[64];
#pragma unroll 1
      for (int half = 0; half < 2; half++) {
        if (half) C.stage_out<false>(acc, 1.f, 1.f);
        proj_unit<true>(C, cur, a, acc, half, true);
        TL(half ? 13 + C.w * 2 : 2 + C.w * 16);
#pragma unroll 1
        for (int u = half ? 5 : 1; u < 8; u++) {
          C.stage_out<false>(acc, 1.f, 1.f);
          proj_unit<false>(C, cur, a, acc, true, u < 7 || !half);
        }
        if (half == 0) TL(12 + C.w * 2);
      }
#pragma unroll
      for (int i = 0; i < 32; i++) A.q[i] = pack_bf16(acc[2 * i], acc[2 * i + 1]);
    }
    TL(C.w * 16 + 3);
    {
      const int rel = 64 * C.w + 16 * wi + (lane >> 2) - 2 * (lane & 3);
      int it = 0, j = rb, b = 1;
      bool pub = false;
      round_first(C, A, cur, j == 0, rel);
#pragma unroll 1
      for (int n = 0; n < 33; n++, b++) {
        float a[4];
        if (b > j) {
          TL(C.w * 16 + 4 + it);
          const int pj = j;
          it++; j = 15 - j; b = 0;
          round_begin(C, A, cur, !(pj & 1), pj > 0, pub, j == 0, rel, a);
          pub = true;
        } else {
          if (b == j && C.w == 0) round_step<true>(C, A, cur, b > 1, pub, true, wiu, a);
          else round_step<false>(C, A, cur, b > 1, pub, b == j, wiu, a);
          pub = false;
        }
        const float b0 = a[0] + a[1], b1 = a[2] + a[3];
        if (__builtin_expect(__any_sync(~0u, !(b0 + b1 <= SUM_LIMIT)), 0))
          redo_block(A, g_qkv + (size_t)((NH + 4 * g + it) * 16 + b) * TILE, b == j, rel, C.zero);
        else { A.l0 += b0; A.l1 += b1; }
      }
      TL(C.w * 16 + 7);
      const bool skip = !(j & 1);
      if (skip) { C.skip(cur); cur.adv(); }
      const Cur cv = cur; cur.adv();
      C.wait(cv);
      C.turn_begin();
      issue_pv(A, C.dsc(cv), j > 0, C.w);
      C.turn_end();
      if (pub) C.publish();
      C.stage_acquire();
      float r0, r1;
      inv_sums(A, r0, r1);
      wg_wait<0>();
      reg_fence(A.o);
      C.release(cv);
      C.stage_out<true>(A.o, r0, r1);
      C.publish();
      if (skip) { C.skip(cur); cur.adv(); }
      if (C.w == 0) C.turn_begin();
    }
    TL(C.w * 16 + 8);
    {
      float acc[64];
      Cur prev = cur;
#pragma unroll 1
      for (int h = 0; h < 32; h++) {
        const Cur cs = cur; cur.adv();
        C.wait(cs);
        wg_fence();
        const uint32_t da = C.dsc(cs) + C.w * 512, db = C.dsc(cs) + (HALF >> 4) - ((8192 >> 4) << 16);
#pragma unroll
        for (int kk = 0; kk < 4; kk++)
          wgmma_ss_n128<1>(acc, desc(da + ((kk * 32) >> 4)), desc(db + ((kk * 2048) >> 4)), kk > 0 ? 1 : h);
        wg_commit();
        wg_wait<1>();
        if (h > 0) C.release(prev);
        prev = cs;
      }
      const Cur cr = cur;
      C.wait(cr);
      uint32_t xr[16], nr[16];
      const uint32_t xa = C.addr(cr) + C.w * 8192;
#pragma unroll
      for (int jj = 0; jj < 4; jj++) {
        ldsm4(xa + C.frag(jj, 0), xr[4 * jj], xr[4 * jj + 1], xr[4 * jj + 2], xr[4 * jj + 3]);
        ldsm4(xa + HALF + C.frag(jj, 0), nr[4 * jj], nr[4 * jj + 1], nr[4 * jj + 2], nr[4 * jj + 3]);
      }
      uint4* mine = g_part + (size_t)(blockIdx.x * 2 + C.w) * 1024 + t;
      const uint4* theirs = g_part + (size_t)((blockIdx.x ^ 64) * 2 + C.w) * 1024 + t;
      const uint32_t tag = ep & 3;
      wg_wait<0>();
      reg_fence(acc);
      TL(C.w * 16 + 9);
#pragma unroll
      for (int i = 0; i < 8; i++) st_tagged(mine + i * 128, (__float_as_uint(acc[32 + 4 * i]) & ~3u) | tag, acc[33 + 4 * i], acc[34 + 4 * i], acc[35 + 4 * i]);
      C.release(prev); C.release(cr);
      uint4 v[8];
      for (int n = 0; n < SPIN_LIMIT; n++) {
        v[7] = ld_tagged(theirs + 7 * 128);
        if (!__all_sync(~0u, (v[7].x & 3) == tag)) continue;
        bool ok = true;
#pragma unroll
        for (int i = 0; i < 7; i++) v[i] = ld_tagged(theirs + i * 128);
#pragma unroll
        for (int i = 0; i < 7; i++) ok &= (v[i].x & 3) == tag;
        if (__all_sync(~0u, ok)) break;
      }
      TL(C.w * 16 + 10);
#pragma unroll
      for (int i = 0; i < 8; i++) {
        xr[2 * i] = add_bf16x2(add_bf16x2(xr[2 * i], pack_bf16(acc[4 * i] + __uint_as_float(v[i].x), acc[4 * i + 1] + __uint_as_float(v[i].y))), nr[2 * i]);
        xr[2 * i + 1] = add_bf16x2(add_bf16x2(xr[2 * i + 1], pack_bf16(acc[4 * i + 2] + __uint_as_float(v[i].z), acc[4 * i + 3] + __uint_as_float(v[i].w))), nr[2 * i + 1]);
      }
#pragma unroll
      for (int jj = 0; jj < 4; jj++) stsm4(xa + C.frag(jj, 0), xr[4 * jj], xr[4 * jj + 1], xr[4 * jj + 2], xr[4 * jj + 3]);
      __syncwarp();
      __nv_bfloat16* po = P.out + (size_t)(j3 * 128 + 64 * C.w + 16 * wi + (lane >> 3)) * DM + ncol * 128 + 64 * ks + (lane & 7) * 8;
#pragma unroll
      for (int i = 0; i < 4; i++) {
        const int row = 16 * wi + 4 * i + (lane >> 3);
        uint4 y;
        asm volatile("ld.shared.v4.u32 {%0, %1, %2, %3}, [%4];" : "=r"(y.x), "=r"(y.y), "=r"(y.z), "=r"(y.w) : "r"(xa + row * 128 + (((lane ^ row) & 7) << 4)) : "memory");
        *(uint4*)(po + 4 * i * DM) = y;
      }
      TL(C.w * 16 + 11);
    }
  }
}

typedef CUresult (*EncodeFn)(CUtensorMap*, CUtensorMapDataType, cuuint32_t, void*, const cuuint64_t*, const cuuint64_t*,
                             const cuuint32_t*, const cuuint32_t*, CUtensorMapInterleave, CUtensorMapSwizzle,
                             CUtensorMapL2promotion, CUtensorMapFloatOOBfill);

void make_map(EncodeFn fn, CUtensorMap* m, const void* ptr, uint64_t cols, uint64_t rows, uint32_t box_rows) {
  cuuint64_t dims[2] = {cols, rows};
  cuuint64_t strides[1] = {cols * 2};
  cuuint32_t box[2] = {64, box_rows};
  cuuint32_t es[2] = {1, 1};
  fn(m, CU_TENSOR_MAP_DATA_TYPE_BFLOAT16, 2, const_cast<void*>(ptr), dims, strides, box, es, CU_TENSOR_MAP_INTERLEAVE_NONE,
     CU_TENSOR_MAP_SWIZZLE_128B, CU_TENSOR_MAP_L2_PROMOTION_L2_128B, CU_TENSOR_MAP_FLOAT_OOB_FILL_NONE);
}

}

extern "C" void kernel_launch(void* const* d_in, const int* in_sizes, int n_in, void* d_out, int out_size) {
  static EncodeFn fn = nullptr;
  static void* xn_ptr = nullptr;
  if (!fn) {
    void* f = nullptr;
    cudaDriverEntryPointQueryResult qr;
    cudaGetDriverEntryPoint("cuTensorMapEncodeTiled", &f, cudaEnableDefault, &qr);
    fn = (EncodeFn)f;
    cudaGetSymbolAddress(&xn_ptr, g_xn);
    cudaFuncSetAttribute(fused_kernel, cudaFuncAttributeMaxDynamicSharedMemorySize, SMEM_TOTAL);
  }
  Params P;
  make_map(fn, &P.x, d_in[0], DM, SEQ, 128);
  make_map(fn, &P.ckv, d_in[1], DM, SEQ, 128);
  make_map(fn, &P.xn, xn_ptr, DM, SEQ, 128);
  make_map(fn, &P.wq, d_in[2], NH * 128, DM, 128);
  make_map(fn, &P.wuk, d_in[3], NH * 128, DM, 128);
  make_map(fn, &P.wuv, d_in[4], NH * 128, DM, 128);
  make_map(fn, &P.wo, d_in[5], DM, NH * 128, 64);
  P.out = (__nv_bfloat16*)d_out;
  P.pwo = (const __nv_bfloat16*)d_in[5];
  P.neg = -1.f;
  P.zero = 0;
  P.px = (const __nv_bfloat16*)d_in[0];
  P.w_r = (const __nv_bfloat16*)d_in[7];
  P.w_gate = (const __nv_bfloat16*)d_in[8];
  P.w_up = (const __nv_bfloat16*)d_in[9];
  P.w_down = (const __nv_bfloat16*)d_in[10];
  fused_kernel<<<NCTA, 384, SMEM_TOTAL>>>(P);
}
```

```cpp
#include <cuda_runtime.h>
#include <cuda_bf16.h>
#include <cuda.h>
#include <stdint.h>

namespace {

constexpr int SEQ = 2048, DM = 512, NH = 32, FF = 1376;
constexpr int NSLOT = 6;
constexpr int TILE = 32768;
constexpr int HALF = 16384;
constexpr int SMEM_STG = NSLOT * TILE;
constexpr int SMEM_BAR = SMEM_STG + 32768;
constexpr int SMEM_WR = SMEM_BAR + 256;
constexpr int SMEM_TOTAL = SMEM_WR + 1024 + 1024;
constexpr int NCTA = 132;
constexpr int LN0 = 2;
constexpr int NSL = 50;
constexpr int KSH = 2;
constexpr int LEAD = 4;
constexpr int MID = 10;
constexpr int MIDB = 7;
constexpr int SPIN_LIMIT = 1 << 17;

constexpr int F_LN = 0;
constexpr int F_GRP = 16;
constexpr int F_CTX = 44;
constexpr int F_FFN = 40;
constexpr int F_MOE = 41;
constexpr int F_VD = 42;
constexpr int F_GU = 43;
constexpr int F_COUNT = 140;

__device__ __align__(1024) __nv_bfloat16 g_xn[SEQ * DM];
__device__ float g_r[SEQ];
__device__ __align__(1024) uint8_t g_qkv[3ull * NH * 16 * TILE + (2 << 20)];
__device__ __align__(1024) uint4 g_part[128 * 8 * 128];
__device__ __align__(16) float g_ypart[4 * DM];
__device__ __align__(16) float g_gu[8 * FF];
__device__ unsigned g_flags[F_COUNT * 32];
__device__ unsigned g_epoch[NCTA];

__device__ __forceinline__ uint32_t smem_u32(const void* p) { return (uint32_t)__cvta_generic_to_shared(p); }
__device__ __forceinline__ void mbar_init(uint32_t bar, int cnt) { asm volatile("mbarrier.init.shared::cta.b64 [%0], %1;" :: "r"(bar), "r"(cnt)); }
__device__ __forceinline__ void mbar_arrive(uint32_t bar) { asm volatile("mbarrier.arrive.shared::cta.b64 _, [%0];" :: "r"(bar) : "memory"); }
__device__ __forceinline__ void mbar_arrive_cluster_if(uint32_t bar, bool pred) {
  asm volatile("{\n.reg .pred p;\nsetp.ne.b32 p, %1, 0;\n@p mbarrier.arrive.shared::cluster.b64 _, [%0];\n}" :: "r"(bar), "r"((int)pred) : "memory");
}
__device__ __forceinline__ void mbar_expect(uint32_t bar, int bytes) { asm volatile("mbarrier.arrive.expect_tx.shared::cta.b64 _, [%0], %1;" :: "r"(bar), "r"(bytes) : "memory"); }
__device__ __forceinline__ void mbar_wait(uint32_t bar, uint32_t parity) {
  asm volatile("{\n.reg .pred p, q;\n.reg .b32 n;\n"
               "mbarrier.try_wait.parity.shared::cta.b64 p, [%0], %1;\n@p bra DONE;\nmov.b32 n, 0;\n"
               "LOOP:\nmbarrier.try_wait.parity.shared::cta.b64 p, [%0], %1;\nadd.s32 n, n, 1;\nsetp.lt.s32 q, n, %2;\n@p bra DONE;\n@q bra LOOP;\n"
               "DONE:\n}" :: "r"(bar), "r"(parity), "n"(SPIN_LIMIT) : "memory");
}
__device__ __forceinline__ void bulk_load(uint32_t dst, const void* src, int bytes, uint32_t bar) {
  asm volatile("cp.async.bulk.shared::cluster.global.mbarrier::complete_tx::bytes [%0], [%1], %2, [%3];" :: "r"(dst), "l"(src), "r"(bytes), "r"(bar) : "memory");
}
__device__ __forceinline__ void bulk_load_mc(uint32_t dst, const void* src, int bytes, uint32_t bar) {
  asm volatile("cp.async.bulk.shared::cluster.global.mbarrier::complete_tx::bytes.multicast::cluster [%0], [%1], %2, [%3], %4;" :: "r"(dst), "l"(src), "r"(bytes), "r"(bar), "h"((uint16_t)3) : "memory");
}
__device__ __forceinline__ void tma_load(uint32_t dst, const CUtensorMap* map, int c0, int c1, uint32_t bar) {
  asm volatile("cp.async.bulk.tensor.2d.shared::cluster.global.mbarrier::complete_tx::bytes [%0], [%1, {%3, %4}], [%2];" :: "r"(dst), "l"(map), "r"(bar), "r"(c0), "r"(c1) : "memory");
}
__device__ __forceinline__ void tma_load_mc(uint32_t dst, const CUtensorMap* map, int c0, int c1, uint32_t bar) {
  asm volatile("cp.async.bulk.tensor.2d.shared::cluster.global.mbarrier::complete_tx::bytes.multicast::cluster [%0], [%1, {%3, %4}], [%2], %5;" :: "r"(dst), "l"(map), "r"(bar), "r"(c0), "r"(c1), "h"((uint16_t)3) : "memory");
}
__device__ __forceinline__ void bulk_store(void* dst, uint32_t src, int bytes) {
  asm volatile("cp.async.bulk.global.shared::cta.bulk_group [%0], [%1], %2;" :: "l"(dst), "r"(src), "r"(bytes) : "memory");
}
__device__ __forceinline__ void st_msg(uint4* p, uint32_t a, uint32_t b, uint32_t c, uint32_t d) {
  asm volatile("{\n.reg .b128 v;\n.reg .b64 lo, hi;\nmov.b64 lo, {%1, %2};\nmov.b64 hi, {%3, %4};\nmov.b128 v, {lo, hi};\n"
               "st.relaxed.gpu.global.b128 [%0], v;\n}" :: "l"(p), "r"(a), "r"(b), "r"(c), "r"(d) : "memory");
}
__device__ __forceinline__ uint4 ld_msg(const uint4* p) {
  uint4 r;
  asm volatile("{\n.reg .b128 v;\n.reg .b64 lo, hi;\nld.relaxed.gpu.global.b128 v, [%4];\nmov.b128 {lo, hi}, v;\n"
               "mov.b64 {%0, %1}, lo;\nmov.b64 {%2, %3}, hi;\n}" : "=r"(r.x), "=r"(r.y), "=r"(r.z), "=r"(r.w) : "l"(p) : "memory");
  return r;
}
__device__ __forceinline__ void l2_prefetch(const void* p, int bytes) { asm volatile("cp.async.bulk.prefetch.L2.global [%0], %1;" :: "l"(p), "r"(bytes) : "memory"); }
__device__ __forceinline__ void tma_prefetch(const CUtensorMap* map, int c0, int c1) {
  asm volatile("cp.async.bulk.prefetch.tensor.2d.L2.global [%0, {%1, %2}];" :: "l"(map), "r"(c0), "r"(c1) : "memory");
}
__device__ __forceinline__ void fence_async_smem() { asm volatile("fence.proxy.async.shared::cta;" ::: "memory"); }
__device__ __forceinline__ void fence_async_global() { asm volatile("fence.proxy.async.global;" ::: "memory"); }
__device__ __forceinline__ void flag_add(int f) { asm volatile("red.release.gpu.global.add.u32 [%0], 1;" :: "l"(&g_flags[f * 32]) : "memory"); }
template <int SLEEP = NSL> __device__ __forceinline__ void flag_wait(int f, unsigned target) {
  const unsigned* p = &g_flags[f * 32];
  unsigned v;
#pragma unroll 1
  for (int n = 0; n < SPIN_LIMIT; ++n) {
    asm volatile("ld.acquire.gpu.global.u32 %0, [%1];" : "=r"(v) : "l"(p) : "memory");
    if ((int)(v - target) >= 0) break;
    __nanosleep(SLEEP);
  }
}
__device__ __forceinline__ bool elect_one() {
  uint32_t p;
  asm volatile("{\n.reg .pred p;\nelect.sync _|p, 0xffffffff;\nselp.b32 %0, 1, 0, p;\n}" : "=r"(p));
  return p;
}
__device__ __forceinline__ void bar_sync(int id, int n) { asm volatile("bar.sync %0, %1;" :: "r"(id), "r"(n) : "memory"); }
__device__ __forceinline__ void bar_arrive(int id, int n) { asm volatile("bar.arrive %0, %1;" :: "r"(id), "r"(n) : "memory"); }
__device__ __forceinline__ void wg_fence() { asm volatile("wgmma.fence.sync.aligned;" ::: "memory"); }
__device__ __forceinline__ void wg_commit() { asm volatile("wgmma.commit_group.sync.aligned;" ::: "memory"); }
template <int N> __device__ __forceinline__ void wg_wait() { asm volatile("wgmma.wait_group.sync.aligned %0;" :: "n"(N) : "memory"); }
template <int N> __device__ __forceinline__ void reg_fence(float (&d)[N]) {
#pragma unroll
  for (int i = 0; i < N; i++) asm volatile("" : "+f"(d[i]) :: "memory");
}
__device__ __forceinline__ void ldsm4(uint32_t addr, uint32_t& r0, uint32_t& r1, uint32_t& r2, uint32_t& r3) {
  asm volatile("ldmatrix.sync.aligned.m8n8.x4.shared.b16 {%0, %1, %2, %3}, [%4];" : "=r"(r0), "=r"(r1), "=r"(r2), "=r"(r3) : "r"(addr) : "memory");
}
__device__ __forceinline__ void stsm4(uint32_t addr, uint32_t r0, uint32_t r1, uint32_t r2, uint32_t r3) {
  asm volatile("stmatrix.sync.aligned.m8n8.x4.shared.b16 [%0], {%1, %2, %3, %4};" :: "r"(addr), "r"(r0), "r"(r1), "r"(r2), "r"(r3) : "memory");
}
__device__ __forceinline__ uint32_t pack_bf16(float lo, float hi) {
  uint32_t r; asm("cvt.rn.bf16x2.f32 %0, %1, %2;" : "=r"(r) : "f"(hi), "f"(lo)); return r;
}
__device__ __forceinline__ float ex2(float x) { float y; asm("ex2.approx.ftz.f32 %0, %1;" : "=f"(y) : "f"(x)); return y; }
__device__ __forceinline__ float bf_lo(uint32_t v) { return __uint_as_float(v << 16); }
__device__ __forceinline__ float bf_hi(uint32_t v) { return __uint_as_float(v & 0xffff0000u); }
__device__ __forceinline__ uint32_t add_bf16x2(uint32_t a, uint32_t b) { uint32_t r; asm("add.rn.bf16x2 %0, %1, %2;" : "=r"(r) : "r"(a), "r"(b)); return r; }
__device__ __forceinline__ float rbf(float x) { return __uint_as_float(pack_bf16(0.f, x)); }

__device__ __forceinline__ uint32_t desc_lo(uint32_t addr) { return ((addr & 0x3FFFF) >> 4) | ((uint32_t)(HALF >> 4) << 16); }
__device__ __forceinline__ uint64_t desc(uint32_t lo) { return (uint64_t)lo | ((uint64_t)(64u | (1u << 30)) << 32); }

template<int TB> __device__ __forceinline__ void wgmma_ss_n128(float (&d)[64], uint64_t descA, uint64_t descB, int scaleD) {
  asm volatile("{\n.reg .pred p;\nsetp.ne.b32 p, %66, 0;\n"
    "wgmma.mma_async.sync.aligned.m64n128k16.f32.bf16.bf16 "
    "{%0, %1, %2, %3, %4, %5, %6, %7, %8, %9, %10, %11, %12, %13, %14, %15, "
    "%16, %17, %18, %19, %20, %21, %22, %23, %24, %25, %26, %27, %28, %29, %30, %31, "
    "%32, %33, %34, %35, %36, %37, %38, %39, %40, %41, %42, %43, %44, %45, %46, %47, "
    "%48, %49, %50, %51, %52, %53, %54, %55, %56, %57, %58, %59, %60, %61, %62, %63}, "
    "%64, %65, p, 1, 1, 0, %67;\n}\n"
    : "+f"(d[0]), "+f"(d[1]), "+f"(d[2]), "+f"(d[3]), "+f"(d[4]), "+f"(d[5]), "+f"(d[6]), "+f"(d[7]),
      "+f"(d[8]), "+f"(d[9]), "+f"(d[10]), "+f"(d[11]), "+f"(d[12]), "+f"(d[13]), "+f"(d[14]), "+f"(d[15]),
      "+f"(d[16]), "+f"(d[17]), "+f"(d[18]), "+f"(d[19]), "+f"(d[20]), "+f"(d[21]), "+f"(d[22]), "+f"(d[23]),
      "+f"(d[24]), "+f"(d[25]), "+f"(d[26]), "+f"(d[27]), "+f"(d[28]), "+f"(d[29]), "+f"(d[30]), "+f"(d[31]),
      "+f"(d[32]), "+f"(d[33]), "+f"(d[34]), "+f"(d[35]), "+f"(d[36]), "+f"(d[37]), "+f"(d[38]), "+f"(d[39]),
      "+f"(d[40]), "+f"(d[41]), "+f"(d[42]), "+f"(d[43]), "+f"(d[44]), "+f"(d[45]), "+f"(d[46]), "+f"(d[47]),
      "+f"(d[48]), "+f"(d[49]), "+f"(d[50]), "+f"(d[51]), "+f"(d[52]), "+f"(d[53]), "+f"(d[54]), "+f"(d[55]),
      "+f"(d[56]), "+f"(d[57]), "+f"(d[58]), "+f"(d[59]), "+f"(d[60]), "+f"(d[61]), "+f"(d[62]), "+f"(d[63])
    : "l"(descA), "l"(descB), "r"(scaleD), "n"(TB));
}

template<int TB> __device__ __forceinline__ void wgmma_rs_n128(float (&d)[64], uint32_t a0, uint32_t a1, uint32_t a2, uint32_t a3, uint64_t descB, int scaleD) {
  asm volatile("{\n.reg .pred p;\nsetp.ne.b32 p, %69, 0;\n"
    "wgmma.mma_async.sync.aligned.m64n128k16.f32.bf16.bf16 "
    "{%0, %1, %2, %3, %4, %5, %6, %7, %8, %9, %10, %11, %12, %13, %14, %15, "
    "%16, %17, %18, %19, %20, %21, %22, %23, %24, %25, %26, %27, %28, %29, %30, %31, "
    "%32, %33, %34, %35, %36, %37, %38, %39, %40, %41, %42, %43, %44, %45, %46, %47, "
    "%48, %49, %50, %51, %52, %53, %54, %55, %56, %57, %58, %59, %60, %61, %62, %63}, "
    "{%64, %65, %66, %67}, %68, p, 1, 1, %70;\n}\n"
    : "+f"(d[0]), "+f"(d[1]), "+f"(d[2]), "+f"(d[3]), "+f"(d[4]), "+f"(d[5]), "+f"(d[6]), "+f"(d[7]),
      "+f"(d[8]), "+f"(d[9]), "+f"(d[10]), "+f"(d[11]), "+f"(d[12]), "+f"(d[13]), "+f"(d[14]), "+f"(d[15]),
      "+f"(d[16]), "+f"(d[17]), "+f"(d[18]), "+f"(d[19]), "+f"(d[20]), "+f"(d[21]), "+f"(d[22]), "+f"(d[23]),
      "+f"(d[24]), "+f"(d[25]), "+f"(d[26]), "+f"(d[27]), "+f"(d[28]), "+f"(d[29]), "+f"(d[30]), "+f"(d[31]),
      "+f"(d[32]), "+f"(d[33]), "+f"(d[34]), "+f"(d[35]), "+f"(d[36]), "+f"(d[37]), "+f"(d[38]), "+f"(d[39]),
      "+f"(d[40]), "+f"(d[41]), "+f"(d[42]), "+f"(d[43]), "+f"(d[44]), "+f"(d[45]), "+f"(d[46]), "+f"(d[47]),
      "+f"(d[48]), "+f"(d[49]), "+f"(d[50]), "+f"(d[51]), "+f"(d[52]), "+f"(d[53]), "+f"(d[54]), "+f"(d[55]),
      "+f"(d[56]), "+f"(d[57]), "+f"(d[58]), "+f"(d[59]), "+f"(d[60]), "+f"(d[61]), "+f"(d[62]), "+f"(d[63])
    : "r"(a0), "r"(a1), "r"(a2), "r"(a3), "l"(descB), "r"(scaleD), "n"(TB));
}

template<int TB> __device__ __forceinline__ void wgmma_rs_n64(float (&d)[32], uint32_t a0, uint32_t a1, uint32_t a2, uint32_t a3, uint64_t descB, int scaleD) {
  asm volatile("{\n.reg .pred p;\nsetp.ne.b32 p, %37, 0;\n"
    "wgmma.mma_async.sync.aligned.m64n64k16.f32.bf16.bf16 "
    "{%0, %1, %2, %3, %4, %5, %6, %7, %8, %9, %10, %11, %12, %13, %14, %15, "
    "%16, %17, %18, %19, %20, %21, %22, %23, %24, %25, %26, %27, %28, %29, %30, %31}, "
    "{%32, %33, %34, %35}, %36, p, 1, 1, %38;\n}\n"
    : "+f"(d[0]), "+f"(d[1]), "+f"(d[2]), "+f"(d[3]), "+f"(d[4]), "+f"(d[5]), "+f"(d[6]), "+f"(d[7]),
      "+f"(d[8]), "+f"(d[9]), "+f"(d[10]), "+f"(d[11]), "+f"(d[12]), "+f"(d[13]), "+f"(d[14]), "+f"(d[15]),
      "+f"(d[16]), "+f"(d[17]), "+f"(d[18]), "+f"(d[19]), "+f"(d[20]), "+f"(d[21]), "+f"(d[22]), "+f"(d[23]),
      "+f"(d[24]), "+f"(d[25]), "+f"(d[26]), "+f"(d[27]), "+f"(d[28]), "+f"(d[29]), "+f"(d[30]), "+f"(d[31])
    : "r"(a0), "r"(a1), "r"(a2), "r"(a3), "l"(descB), "r"(scaleD), "n"(TB));
}

template<int TB> __device__ __forceinline__ void wgmma_rs_n128_init(float (&d)[64], uint32_t a0, uint32_t a1, uint32_t a2, uint32_t a3, uint64_t descB, int scaleD) {
  asm volatile("{\n.reg .pred p;\nsetp.ne.b32 p, %69, 0;\n"
    "wgmma.mma_async.sync.aligned.m64n128k16.f32.bf16.bf16 "
    "{%0, %1, %2, %3, %4, %5, %6, %7, %8, %9, %10, %11, %12, %13, %14, %15, "
    "%16, %17, %18, %19, %20, %21, %22, %23, %24, %25, %26, %27, %28, %29, %30, %31, "
    "%32, %33, %34, %35, %36, %37, %38, %39, %40, %41, %42, %43, %44, %45, %46, %47, "
    "%48, %49, %50, %51, %52, %53, %54, %55, %56, %57, %58, %59, %60, %61, %62, %63}, "
    "{%64, %65, %66, %67}, %68, p, 1, 1, %70;\n}\n"
    : "=f"(d[0]), "=f"(d[1]), "=f"(d[2]), "=f"(d[3]), "=f"(d[4]), "=f"(d[5]), "=f"(d[6]), "=f"(d[7]),
      "=f"(d[8]), "=f"(d[9]), "=f"(d[10]), "=f"(d[11]), "=f"(d[12]), "=f"(d[13]), "=f"(d[14]), "=f"(d[15]),
      "=f"(d[16]), "=f"(d[17]), "=f"(d[18]), "=f"(d[19]), "=f"(d[20]), "=f"(d[21]), "=f"(d[22]), "=f"(d[23]),
      "=f"(d[24]), "=f"(d[25]), "=f"(d[26]), "=f"(d[27]), "=f"(d[28]), "=f"(d[29]), "=f"(d[30]), "=f"(d[31]),
      "=f"(d[32]), "=f"(d[33]), "=f"(d[34]), "=f"(d[35]), "=f"(d[36]), "=f"(d[37]), "=f"(d[38]), "=f"(d[39]),
      "=f"(d[40]), "=f"(d[41]), "=f"(d[42]), "=f"(d[43]), "=f"(d[44]), "=f"(d[45]), "=f"(d[46]), "=f"(d[47]),
      "=f"(d[48]), "=f"(d[49]), "=f"(d[50]), "=f"(d[51]), "=f"(d[52]), "=f"(d[53]), "=f"(d[54]), "=f"(d[55]),
      "=f"(d[56]), "=f"(d[57]), "=f"(d[58]), "=f"(d[59]), "=f"(d[60]), "=f"(d[61]), "=f"(d[62]), "=f"(d[63])
    : "r"(a0), "r"(a1), "r"(a2), "r"(a3), "l"(descB), "r"(scaleD), "n"(TB));
}

template<int TB> __device__ __forceinline__ void wgmma_rs_n64_init(float (&d)[32], uint32_t a0, uint32_t a1, uint32_t a2, uint32_t a3, uint64_t descB, int scaleD) {
  asm volatile("{\n.reg .pred p;\nsetp.ne.b32 p, %37, 0;\n"
    "wgmma.mma_async.sync.aligned.m64n64k16.f32.bf16.bf16 "
    "{%0, %1, %2, %3, %4, %5, %6, %7, %8, %9, %10, %11, %12, %13, %14, %15, "
    "%16, %17, %18, %19, %20, %21, %22, %23, %24, %25, %26, %27, %28, %29, %30, %31}, "
    "{%32, %33, %34, %35}, %36, p, 1, 1, %38;\n}\n"
    : "=f"(d[0]), "=f"(d[1]), "=f"(d[2]), "=f"(d[3]), "=f"(d[4]), "=f"(d[5]), "=f"(d[6]), "=f"(d[7]),
      "=f"(d[8]), "=f"(d[9]), "=f"(d[10]), "=f"(d[11]), "=f"(d[12]), "=f"(d[13]), "=f"(d[14]), "=f"(d[15]),
      "=f"(d[16]), "=f"(d[17]), "=f"(d[18]), "=f"(d[19]), "=f"(d[20]), "=f"(d[21]), "=f"(d[22]), "=f"(d[23]),
      "=f"(d[24]), "=f"(d[25]), "=f"(d[26]), "=f"(d[27]), "=f"(d[28]), "=f"(d[29]), "=f"(d[30]), "=f"(d[31])
    : "r"(a0), "r"(a1), "r"(a2), "r"(a3), "l"(descB), "r"(scaleD), "n"(TB));
}

struct Cur {
  uint32_t o, phase;
  __device__ __forceinline__ void adv() { o += 8; if (o == 8 * NSLOT) { o = 0; phase ^= 1; } }
};

__device__ __forceinline__ int item_rows(int rb, int it) { const int x = rb ^ ((it & 2) << 2); return (it & 1) ? 15 - x : x; }

struct Params {
  CUtensorMap ckv, xn, x64, xn64, wq, wuk, wuv, wo;
  __nv_bfloat16* out;
  const __nv_bfloat16 *px, *w_r, *w_gate, *w_up, *w_down;
  uint8_t* qkv;
  float neg;
  uint32_t zero;
  int role[NCTA / 2];
  __device__ __forceinline__ uint8_t* tile(int kind, int head, int j) const {
    return qkv + (size_t)((kind * NH + head) * 16 + j) * TILE;
  }
};

struct LayerNorm {
  uint32_t x[16], mb;
  float rs;
  __device__ __forceinline__ void load(const __nv_bfloat16* row) {
#pragma unroll
    for (int i = 0; i < 4; i++)
      asm volatile("ld.volatile.global.v4.u32 {%0, %1, %2, %3}, [%4];" : "=r"(x[4 * i]), "=r"(x[4 * i + 1]), "=r"(x[4 * i + 2]), "=r"(x[4 * i + 3]) : "l"(row + 128 * i) : "memory");
  }
  __device__ __forceinline__ void stats() {
    const float x0 = bf_lo(__shfl_sync(~0u, x[0], 0, 16));
    float s0 = 0.f, s1 = 0.f, q0 = 0.f, q1 = 0.f;
#pragma unroll
    for (int k = 0; k < 16; k++) {
      const float d0 = bf_lo(x[k]) - x0, d1 = bf_hi(x[k]) - x0;
      s0 += d0; s1 += d1; q0 = fmaf(d0, d0, q0); q1 = fmaf(d1, d1, q1);
    }
    s0 += s1; q0 += q1;
#pragma unroll
    for (int o = 8; o; o >>= 1) { s0 += __shfl_xor_sync(~0u, s0, o); q0 += __shfl_xor_sync(~0u, q0, o); }
    s0 *= 1.f / DM;
    mb = pack_bf16(x0 + s0, x0 + s0);
    float sd;
    asm("sqrt.approx.f32 %0, %1;" : "=f"(sd) : "f"(rbf(rbf(fmaxf(fmaf(-s0, s0, q0 * (1.f / DM)), 0.f)) + 1e-5f)));
    asm("rcp.approx.f32 %0, %1;" : "=f"(rs) : "f"(rbf(sd)));
  }
  __device__ __forceinline__ void store(__nv_bfloat16* row) {
#pragma unroll
    for (int k = 0; k < 16; k++) {
      uint32_t d;
      asm("sub.rn.bf16x2 %0, %1, %2;" : "=r"(d) : "r"(x[k]), "r"(mb));
      x[k] = pack_bf16(bf_lo(d) * rs, bf_hi(d) * rs);
    }
#pragma unroll
    for (int i = 0; i < 4; i++) *(uint4*)(row + 128 * i) = make_uint4(x[4 * i], x[4 * i + 1], x[4 * i + 2], x[4 * i + 3]);
  }
  __device__ __forceinline__ void route(uint32_t w_smem, float* dst) {
    float s0 = 0.f, s1 = 0.f;
#pragma unroll
    for (int i = 0; i < 4; i++) {
      uint32_t w[4];
      asm volatile("ld.shared.v4.u32 {%0, %1, %2, %3}, [%4];" : "=r"(w[0]), "=r"(w[1]), "=r"(w[2]), "=r"(w[3]) : "r"(w_smem + 256 * i) : "memory");
#pragma unroll
      for (int k = 0; k < 4; k++) { s0 = fmaf(bf_lo(x[4 * i + k]), bf_lo(w[k]), s0); s1 = fmaf(bf_hi(x[4 * i + k]), bf_hi(w[k]), s1); }
    }
    s0 += s1;
#pragma unroll
    for (int o = 8; o; o >>= 1) s0 += __shfl_xor_sync(~0u, s0, o);
    *dst = rbf(s0);
  }
};

__device__ __forceinline__ void fma8(float (&acc)[8], float x, const uint4& a) {
  acc[0] = fmaf(x, bf_lo(a.x), acc[0]); acc[1] = fmaf(x, bf_hi(a.x), acc[1]); acc[2] = fmaf(x, bf_lo(a.y), acc[2]); acc[3] = fmaf(x, bf_hi(a.y), acc[3]);
  acc[4] = fmaf(x, bf_lo(a.z), acc[4]); acc[5] = fmaf(x, bf_hi(a.z), acc[5]); acc[6] = fmaf(x, bf_lo(a.w), acc[6]); acc[7] = fmaf(x, bf_hi(a.w), acc[7]);
}

__device__ __forceinline__ float sigmoidf(float x) { return __fdividef(1.f, 1.f + __expf(-x)); }
__device__ __forceinline__ void moe_cta(const Params& P, int q, unsigned ep, uint8_t* smem) {
  constexpr int CH = 49152, WCH = 44032;
  float* xs = (float*)(smem + 4 * CH);
  float* red = xs + DM;
  unsigned* best = (unsigned*)(red + 4 * DM);
  const uint32_t sb = smem_u32(smem), bars = sb + SMEM_BAR + 128;
  const int tid = threadIdx.x - 128;
  auto fetch = [&](int n) {
    const uint8_t* src = (const uint8_t*)(n < 8 ? P.w_gate : n < 16 ? P.w_up : P.w_down) + (q * 8 + (n & 7)) * WCH;
    mbar_expect(bars + 8 * (n & 3), WCH);
    bulk_load(sb + (n & 3) * CH, src, WCH, bars + 8 * (n & 3));
  };
  if (tid < 16) flag_wait(F_LN + tid, ep * 8);
  if (tid == 0) {
    *best = 0;
#pragma unroll 1
    for (int i = 0; i < 4; i++) fetch(i);
  }
  bar_sync(6, 256);
  unsigned key = 0;
#pragma unroll 2
  for (int i = tid; i < SEQ; i += 256) {
    const unsigned b = __float_as_uint(__ldcg(&g_r[i]) + 0.f);
    key = max(key, ((b ^ (((int)b >> 31) | 0x80000000u)) & 0xffff0000u) | (0xffff - i));
  }
  atomicMax(best, __reduce_max_sync(~0u, key));
  bar_sync(6, 256);
  const int sel = 0xffff - (*best & 0xffff);
  const uint32_t xsel = __ldcg((const uint32_t*)(g_xn + sel * DM) + tid);
  xs[2 * tid] = bf_lo(xsel); xs[2 * tid + 1] = bf_hi(xsel);
#pragma unroll 1
  for (int m = 0; m < 3; m++) {
    if (m == 2) {
      bar_sync(6, 256);
      if (tid == 0) { flag_add(F_GU); flag_wait(F_GU, ep * 4); }
      bar_sync(6, 256);
#pragma unroll 1
      for (int f = tid; f < 344; f += 256) {
        float g = 0.f, u = 0.f;
#pragma unroll
        for (int i = 0; i < 4; i++) { g += __ldcg(&g_gu[2 * i * FF + q * 344 + f]); u += __ldcg(&g_gu[(2 * i + 1) * FF + q * 344 + f]); }
        g = rbf(g);
        xs[f] = rbf(rbf(g * sigmoidf(g)) * rbf(u));
      }
    }
    bar_sync(6, 256);
    float acc[8] = {0.f, 0.f, 0.f, 0.f, 0.f, 0.f, 0.f, 0.f};
    const int rows = m < 2 ? 16 : 43, pitch = m < 2 ? 172 : 64, step = m < 2 ? 1 : 4;
    const int col = m < 2 ? tid : tid & 63, k0 = m < 2 ? (tid < 172 ? 0 : 16) : tid >> 6;
    const float* xv = xs + (m < 2 ? q * 128 : 0);
#pragma unroll 1
    for (int i = 0; i < 8; i++) {
      const int n = 8 * m + i;
      mbar_wait(bars + 8 * (n & 3), (n >> 2) & 1);
      const uint4* w = (const uint4*)(smem + (n & 3) * CH) + col;
#pragma unroll 4
      for (int k = k0; k < rows; k += step) fma8(acc, xv[rows * i + k], w[k * pitch]);
      fence_async_smem();
      bar_sync(6, 256);
      if (tid == 0 && n + 4 < 24) fetch(n + 4);
    }
    float4* d = m < 2 ? (float4*)(g_gu + (q * 2 + m) * FF) : (float4*)red;
    if (k0 < rows) { d[2 * tid] = make_float4(acc[0], acc[1], acc[2], acc[3]); d[2 * tid + 1] = make_float4(acc[4], acc[5], acc[6], acc[7]); }
  }
  bar_sync(6, 256);
  const float2* r2 = (const float2*)red + tid;
  ((float2*)g_ypart)[q * 256 + tid] = make_float2((r2[0].x + r2[256].x) + (r2[512].x + r2[768].x), (r2[0].y + r2[256].y) + (r2[512].y + r2[768].y));
  bar_sync(6, 256);
  if (tid == 0) flag_add(F_FFN);
  if (q == 0) {
    if (tid < 9) flag_wait(tid < 8 ? F_GRP + 3 * tid + 1 : F_FFN, ep * (tid < 8 ? 32 : 4));
    bar_sync(6, 256);
    const float gate = rbf(sigmoidf(__ldcg(&g_r[sel])));
    float2 y[4];
#pragma unroll
    for (int i = 0; i < 4; i++) y[i] = __ldcg((const float2*)g_ypart + 256 * i + tid);
    const uint32_t ys = pack_bf16((y[0].x + y[1].x) + (y[2].x + y[3].x), (y[0].y + y[1].y) + (y[2].y + y[3].y));
    ((uint32_t*)(g_xn + sel * DM))[tid] = add_bf16x2(xsel, pack_bf16(bf_lo(ys) * gate, bf_hi(ys) * gate));
    bar_sync(6, 256);
    if (tid == 0) flag_add(F_MOE);
  }
}

struct Ctx {
  uint32_t sb;
  uint32_t dlo;
  uint32_t full0;
  uint32_t rel;
  bool rel_pred, warp0;
  uint32_t stg;
  uint32_t stg_full, stg_empty;
  uint32_t stg_phase;
  uint32_t frag_off;
  uint32_t frag_x;
  int w;
  float neg;
  uint32_t zero;
  __device__ __forceinline__ void wait(const Cur& c) const { mbar_wait(full0 + c.o, c.phase); }
  __device__ __forceinline__ void release(const Cur& c) const { mbar_arrive_cluster_if(rel + c.o, rel_pred); }
  __device__ __forceinline__ void skip(const Cur& c) const { if (warp0) { wait(c); release(c); } }
  __device__ __forceinline__ uint32_t addr(const Cur& c) const { return sb + c.o * (TILE / 8); }
  __device__ __forceinline__ uint32_t dsc(const Cur& c) const { return dlo + c.o * (TILE / 128); }
  __device__ __forceinline__ void turn_begin(uint32_t dep = 0) { bar_sync(1 + w + dep, 256); }
  __device__ __forceinline__ void turn_end() { bar_arrive(2 - w, 256); }
  __device__ __forceinline__ uint32_t frag(int jj, int hstride) const { return (jj >> 2) * hstride + frag_off + (((jj & 3) * 32) ^ frag_x); }
  __device__ __forceinline__ void set_tracked() const { asm volatile("st.shared.u32 [%0], %1;" :: "r"(full0 + 244 + 4 * w), "r"(1) : "memory"); }
  __device__ __forceinline__ bool tracked() const {
    uint32_t v; asm volatile("ld.shared.u32 %0, [%1];" : "=r"(v) : "r"(full0 + 244 + 4 * w) : "memory");
    return __any_sync(~0u, v);
  }
  __device__ __forceinline__ void stage_acquire() { mbar_wait(stg_empty, stg_phase ^ 1); stg_phase ^= 1; }
  template <bool SCALE> __device__ __forceinline__ void stage_out(const float (&d)[64], float s0, float s1) {
#pragma unroll
    for (int jj = 0; jj < 8; jj++) {
      if (SCALE)
        stsm4(stg + frag(jj, 8192), pack_bf16(d[8 * jj] * s0, d[8 * jj + 1] * s0), pack_bf16(d[8 * jj + 2] * s1, d[8 * jj + 3] * s1),
              pack_bf16(d[8 * jj + 4] * s0, d[8 * jj + 5] * s0), pack_bf16(d[8 * jj + 6] * s1, d[8 * jj + 7] * s1));
      else
        stsm4(stg + frag(jj, 8192), pack_bf16(d[8 * jj], d[8 * jj + 1]), pack_bf16(d[8 * jj + 2], d[8 * jj + 3]),
              pack_bf16(d[8 * jj + 4], d[8 * jj + 5]), pack_bf16(d[8 * jj + 6], d[8 * jj + 7]));
    }
  }
  __device__ __forceinline__ void publish() const { fence_async_smem(); mbar_arrive(stg_full); }
};

constexpr float SM_SCALE = 0.08838834764831845f * 1.4426950408889634f;
constexpr float SUM_MAX = 1152921504606846976.f;
constexpr float SUM_MIN = 9.313225746154785e-10f;

struct Attn {
  float o[64];
  uint32_t p[32], q[32];
  float n0, n1;
  float l0, l1;
  bool tracked;
};

__device__ __forceinline__ void issue_qk(const Attn& A, float (&s)[64], uint32_t d) {
  wg_fence();
  wgmma_rs_n128_init<0>(s, A.q[0], A.q[1], A.q[2], A.q[3], desc(d), 0);
#pragma unroll
  for (int kk = 1; kk < 8; kk++)
    wgmma_rs_n128<0>(s, A.q[4 * kk], A.q[4 * kk + 1], A.q[4 * kk + 2], A.q[4 * kk + 3], desc(d + (((kk >> 2) * HALF + (kk & 3) * 32) >> 4)), 1);
  wg_commit();
}
__device__ __forceinline__ void issue_qk(const Attn& A, float (&s)[32], uint32_t d) {
  wg_fence();
  wgmma_rs_n64_init<0>(s, A.q[0], A.q[1], A.q[2], A.q[3], desc(d), 0);
#pragma unroll
  for (int kk = 1; kk < 8; kk++)
    wgmma_rs_n64<0>(s, A.q[4 * kk], A.q[4 * kk + 1], A.q[4 * kk + 2], A.q[4 * kk + 3], desc(d + (((kk >> 2) * HALF + (kk & 3) * 32) >> 4)), 1);
  wg_commit();
}
template <int NK> __device__ __forceinline__ void issue_pv_n(Attn& A, uint32_t d, int acc) {
  wg_fence();
#pragma unroll
  for (int kk = 0; kk < NK; kk++)
    wgmma_rs_n128<1>(A.o, A.p[4 * kk], A.p[4 * kk + 1], A.p[4 * kk + 2], A.p[4 * kk + 3], desc(d + ((kk * 2048) >> 4)), kk > 0 ? 1 : acc);
  wg_commit();
}
__device__ __forceinline__ void issue_pv(Attn& A, uint32_t d, int acc, bool upper) {
  if (upper) issue_pv_n<8>(A, d, acc); else issue_pv_n<4>(A, d, acc);
}
template <int J0, int J1, int N> __device__ __forceinline__ void pack_p(Attn& A, const float (&s)[N]) {
#pragma unroll
  for (int i = 2 * J0; i < 2 * J1; i++) A.p[i] = pack_bf16(s[2 * i], s[2 * i + 1]);
}
template <int N> __device__ __forceinline__ void add_shift(const Attn& A, float (&s)[N]) {
#pragma unroll
  for (int j = 0; j < N / 4; j++) { s[4 * j] += A.n0; s[4 * j + 1] += A.n0; s[4 * j + 2] += A.n1; s[4 * j + 3] += A.n1; }
}
template <int E0, int E1, int S0, int S1, int N> __device__ __forceinline__ void exp_sum(float (&s)[N], float (&a)[4]) {
#pragma unroll
  for (int i = 4 * E0; i < 4 * E1; i++) s[i] = ex2(s[i]);
#pragma unroll
  for (int i = 4 * S0; i < 4 * S1; i++) a[i & 3] = i < 4 ? s[i] : a[i & 3] + s[i];
}
__device__ __forceinline__ void pin(float v, float neg, uint32_t addr) {
  asm volatile("{\n.reg .pred p;\nsetp.lt.f32 p, %0, %2;\n@p mbarrier.arrive.shared::cta.b64 _, [%1];\n}" :: "f"(v), "r"(addr), "f"(neg) : "memory");
}
template <int J0, int J1, int N> __device__ __forceinline__ void causal_mask(float (&s)[N], int rel) {
#pragma unroll
  for (int j = J0; j < J1; j++) {
    if (8 * j > rel) s[4 * j] = -INFINITY;
    if (8 * j + 1 > rel) s[4 * j + 1] = -INFINITY;
    if (8 * j > rel + 8) s[4 * j + 2] = -INFINITY;
    if (8 * j + 1 > rel + 8) s[4 * j + 3] = -INFINITY;
  }
}
__device__ __forceinline__ void inv_sums(const Attn& A, float& r0, float& r1) {
  float l0 = A.l0, l1 = A.l1;
  l0 += __shfl_xor_sync(~0u, l0, 1); l1 += __shfl_xor_sync(~0u, l1, 1);
  l0 += __shfl_xor_sync(~0u, l0, 2); l1 += __shfl_xor_sync(~0u, l1, 2);
  asm("rcp.approx.ftz.f32 %0, %1;" : "=f"(r0) : "f"(l0));
  asm("rcp.approx.ftz.f32 %0, %1;" : "=f"(r1) : "f"(l1));
}
__device__ __forceinline__ void track_max(Attn& A, float (&s)[64], bool first, float& c0, float& c1) {
  float x0 = fmaxf(s[0], s[1]), x1 = fmaxf(s[2], s[3]);
#pragma unroll
  for (int j = 1; j < 16; j++) { x0 = fmaxf(x0, fmaxf(s[4 * j], s[4 * j + 1])); x1 = fmaxf(x1, fmaxf(s[4 * j + 2], s[4 * j + 3])); }
  x0 = fmaxf(x0, __shfl_xor_sync(~0u, x0, 1)); x1 = fmaxf(x1, __shfl_xor_sync(~0u, x1, 1));
  x0 = fmaxf(x0, __shfl_xor_sync(~0u, x0, 2)); x1 = fmaxf(x1, __shfl_xor_sync(~0u, x1, 2));
  const float n0 = first ? -x0 : fminf(-x0, A.n0), n1 = first ? -x1 : fminf(-x1, A.n1);
  if (!first) { c0 = ex2(n0 - A.n0); c1 = ex2(n1 - A.n1); A.l0 *= c0; A.l1 *= c1; }
  A.n0 = n0; A.n1 = n1;
  add_shift(A, s);
}
__device__ __forceinline__ void redo_block(Attn& A, const uint8_t* ktile, bool first, bool diag, int rel) {
  const int lane = threadIdx.x & 31;
  const uint32_t off = (lane >> 2) * 144 + (lane & 3) * 4;
  float x0 = -INFINITY, x1 = -INFINITY;
  if (!diag) rel = 128;
#pragma unroll 1
  for (int i = 0; i < 16; i++) {
    float s[8] = {0.f, 0.f, 0.f, 0.f, 0.f, 0.f, 0.f, 0.f};
    const uint8_t* kp = ktile + (i & 7) * 2048;
#pragma unroll
    for (int kk = 0; kk < 8; kk++) {
#pragma unroll
      for (int j = 0; j < 2; j++) {
        const uint32_t b0 = __ldca((const uint32_t*)(kp + (off ^ ((kk & 3) * 32)) + j * 1024 + (kk >> 2) * HALF));
        const uint32_t b1 = __ldca((const uint32_t*)(kp + (off ^ ((kk & 3) * 32 + 16)) + j * 1024 + (kk >> 2) * HALF));
        asm("mma.sync.aligned.m16n8k16.row.col.f32.bf16.bf16.f32 {%0, %1, %2, %3}, {%4, %5, %6, %7}, {%8, %9}, {%0, %1, %2, %3};"
            : "+f"(s[4 * j]), "+f"(s[4 * j + 1]), "+f"(s[4 * j + 2]), "+f"(s[4 * j + 3])
            : "r"(A.q[4 * kk]), "r"(A.q[4 * kk + 1]), "r"(A.q[4 * kk + 2]), "r"(A.q[4 * kk + 3]), "r"(b0), "r"(b1));
      }
    }
    causal_mask<0, 2>(s, rel - 16 * (i & 7));
    if (i < 8) {
      x0 = fmaxf(x0, fmaxf(fmaxf(s[0], s[1]), fmaxf(s[4], s[5])));
      x1 = fmaxf(x1, fmaxf(fmaxf(s[2], s[3]), fmaxf(s[6], s[7])));
      if (i == 7) {
        x0 = fmaxf(x0, __shfl_xor_sync(~0u, x0, 1)); x1 = fmaxf(x1, __shfl_xor_sync(~0u, x1, 1));
        x0 = fmaxf(x0, __shfl_xor_sync(~0u, x0, 2)); x1 = fmaxf(x1, __shfl_xor_sync(~0u, x1, 2));
        const float n0 = first ? -x0 : fminf(-x0, A.n0), n1 = first ? -x1 : fminf(-x1, A.n1);
        x0 = first ? 1.f : ex2(n0 - A.n0); x1 = first ? 1.f : ex2(n1 - A.n1);
        A.n0 = n0; A.n1 = n1; A.l0 *= x0; A.l1 *= x1;
      }
    } else {
      float a[4];
      add_shift(A, s);
      exp_sum<0, 2, 0, 2>(s, a);
      A.l0 += a[0] + a[1]; A.l1 += a[2] + a[3];
#pragma unroll
      for (int k = 0; k < 28; k++) A.p[k] = A.p[k + 4];
#pragma unroll
      for (int k = 0; k < 4; k++) A.p[28 + k] = pack_bf16(s[2 * k], s[2 * k + 1]);
    }
  }
#pragma unroll
  for (int j = 0; j < 16; j++) { A.o[4 * j] *= x0; A.o[4 * j + 1] *= x0; A.o[4 * j + 2] *= x1; A.o[4 * j + 3] *= x1; }
}
template <int N> __device__ __forceinline__ uint32_t loaded(const uint32_t* f, uint32_t zero) {
  uint32_t d = 0;
#pragma unroll
  for (int i = 0; i < N; i++) d |= f[4 * i];
  return d & zero;
}
template <int N> __device__ __forceinline__ void round_middle(Ctx& C, Attn& A, float (&s)[N], float (&a)[4], const Cur& cv, const Cur& next) {
  pin((a[0] + a[1]) + (a[2] + a[3]), C.neg, C.stg_full);
  wg_wait<0>();
  C.release(cv);
  C.wait(next);
  reg_fence(A.o);
  reg_fence(s);
}
__device__ __forceinline__ void check_min(float (&a)[4], bool whole_rows) {
  float b0 = a[0] + a[1], b1 = a[2] + a[3];
  if (whole_rows) {
    b0 += __shfl_xor_sync(~0u, b0, 1); b1 += __shfl_xor_sync(~0u, b1, 1);
    b0 += __shfl_xor_sync(~0u, b0, 2); b1 += __shfl_xor_sync(~0u, b1, 2);
  }
  asm("{\n.reg .pred p;\nsetp.lt.f32 p, %1, %2;\nselp.f32 %0, 0f7F800000, %0, p;\n}" : "+f"(a[0]) : "f"(fminf(b0, b1)), "f"(SUM_MIN));
}
__device__ __forceinline__ void round_first(Ctx& C, Attn& A, Cur& cur, bool diag, int rel, float (&a)[4]) {
  const Cur ck = cur; cur.adv();
  C.wait(ck);
  C.turn_begin();
  float s[64];
  issue_qk(A, s, C.dsc(ck));
  C.turn_end();
  if (C.w) bar_sync(7, 256);
  wg_wait<0>();
  reg_fence(s);
  C.release(ck);
  A.l0 = A.l1 = 0.f; A.n0 = A.n1 = 0.f;
  if (diag) causal_mask<0, 16>(s, rel);
  exp_sum<0, 16, 0, 16>(s, a);
  if (!C.w) bar_arrive(7 + (__float_as_uint(a[3]) & C.zero), 256);
  pack_p<0, 16>(A, s);
  check_min(a, diag);
  C.wait(cur);
}
__device__ __forceinline__ void round_begin(Ctx& C, Attn& A, Cur& cur, bool skip, int pv_acc, bool diag, bool short_item, int rel, float (&a)[4]) {
  const Cur cq = cur;
  Cur cv;
  uint32_t q0 = C.stg, q1 = C.stg + 8192;
  if (skip) {
    cur.adv(); cv = cur; cur.adv();
    C.wait(cur);
    q0 = C.addr(cq) + C.w * 8192; q1 = q0 + HALF;
  } else {
    C.stage_acquire();
  }
  const Cur ck = cur; cur.adv();
  const Cur cs = cur; cur.adv();
  if (!skip) cv = cs;
#pragma unroll
  for (int jj = 0; jj < 8; jj++) ldsm4((jj < 4 ? q0 : q1) + C.frag(jj, 0), A.q[4 * jj], A.q[4 * jj + 1], A.q[4 * jj + 2], A.q[4 * jj + 3]);
  C.turn_begin();
  float s[64];
  issue_qk(A, s, C.dsc(ck));
  C.wait(cv);
  A.tracked = C.tracked();
  float r0, r1;
  inv_sums(A, r0, r1);
  pin(r0 + r1, C.neg, C.stg_full);
  issue_pv(A, C.dsc(cv), pv_acc, C.w);
  C.turn_end();
  wg_wait<1>();
  reg_fence(s);
  if (skip) C.release(cq);
  C.release(ck);
  A.l0 = A.l1 = 0.f; A.n0 = A.n1 = 0.f;
  if (diag || A.tracked) {
    causal_mask<0, 16>(s, diag ? rel : 128);
    if (A.tracked) track_max(A, s, true, a[0], a[1]);
  }
  exp_sum<0, MIDB + 2, 0, MIDB>(s, a);
  round_middle(C, A, s, a, cv, cur);
#pragma unroll
  for (int i = 0; i < 64; i++) A.o[i] *= (i & 2) ? r1 : r0;
  exp_sum<MIDB + 2, 16, MIDB, 16>(s, a);
  pack_p<0, 16>(A, s);
  check_min(a, diag || A.tracked);
  if (skip) C.stage_acquire();
  if (short_item) { C.stage_out<false>(A.o, 1.f, 1.f); C.publish(); }
  if (skip) C.skip(cs);
}
template <int KIND> __device__ __forceinline__ void round_step(Ctx& C, Attn& A, Cur& cur, int pv_acc, bool drain, bool pub, int rel, float (&a)[4]) {
  constexpr int NJ = KIND == 2 ? 8 : 16, E = KIND == 2 ? 8 : KIND == 3 ? 4 : MID + 2;
  const Cur ck = cur; cur.adv();
  const Cur cv = cur; cur.adv();
  C.turn_begin();
  float s[4 * NJ];
  issue_qk(A, s, C.dsc(ck));
  if ((KIND == 0 || KIND == 3) && drain) C.stage_out<false>(A.o, 1.f, 1.f);
  if (pub) C.publish();
  C.wait(cv);
  if (KIND != 3) A.tracked = C.tracked();
  issue_pv(A, C.dsc(cv), pv_acc, true);
  C.turn_end();
  wg_wait<1>();
  reg_fence(s);
  C.release(ck);
  float c0, c1;
  if constexpr (KIND == 3) {
    if (rel < 128) causal_mask<0, 16>(s, rel);
    track_max(A, s, false, c0, c1);
  } else if (KIND) {
    causal_mask<NJ - 8, NJ>(s, rel);
  }
  exp_sum<0, E, 0, E - 2>(s, a);
  round_middle(C, A, s, a, cv, cur);
  if (KIND == 3) {
#pragma unroll
    for (int i = 0; i < 64; i++) A.o[i] *= (i & 2) ? c1 : c0;
  }
  exp_sum<E, NJ, E - 2, NJ>(s, a);
  pack_p<0, NJ>(A, s);
}

template <int I> __device__ __forceinline__ void issue_proj(float (&acc)[64], const uint32_t (&a)[128], uint32_t d) {
  wg_fence();
#pragma unroll
  for (int kk = 0; kk < 8; kk++)
    wgmma_rs_n128<1>(acc, a[32 * I + 4 * kk], a[32 * I + 4 * kk + 1], a[32 * I + 4 * kk + 2], a[32 * I + 4 * kk + 3], desc(d + ((kk * 2048) >> 4)), (I | kk) > 0);
  wg_commit();
}
template <int I> __device__ __forceinline__ void proj_load_a(Ctx& C, const Cur& ca, uint32_t (&a)[128]) {
  C.wait(ca);
  const uint32_t aa = C.addr(ca) + C.w * 8192;
#pragma unroll
  for (int jj = 0; jj < 8; jj++) ldsm4(aa + C.frag(jj, HALF), a[32 * I + 4 * jj], a[32 * I + 4 * jj + 1], a[32 * I + 4 * jj + 2], a[32 * I + 4 * jj + 3]);
}
template <int I> __device__ __forceinline__ void proj_step_first(Ctx& C, Cur& cur, uint32_t (&a)[128], float (&acc)[64], LayerNorm& ln, const __nv_bfloat16* px, int ln_off) {
  const Cur ca = cur; cur.adv();
  const Cur cb = cur; cur.adv();
  if (I == 0) proj_load_a<0>(C, ca, a);
  C.wait(cb);
  C.turn_begin(loaded<8>(a + 32 * I, C.zero));
  C.release(ca);
  issue_proj<I>(acc, a, C.dsc(cb));
  C.turn_end();
  if (I == LN0) ln.load(px + ln_off);
  if (I == 3) C.stage_acquire(); else proj_load_a<(I + 1) & 3>(C, cur, a);
  wg_wait<0>();
  reg_fence(acc);
  C.release(cb);
}
template <int I, class F> __device__ __forceinline__ void proj_step2(Ctx& C, Cur& cur, uint32_t (&a)[128], float (&acc)[64], bool acq, bool reload, F&& shadow) {
  const Cur c0 = cur; cur.adv();
  const Cur c1 = cur; cur.adv();
  C.wait(c0);
  C.turn_begin();
  issue_proj<I>(acc, a, C.dsc(c0));
  C.wait(c1);
  issue_proj<I + 1>(acc, a, C.dsc(c1));
  C.turn_end();
  wg_wait<1>();
  C.release(c0);
  if (I == 0) C.publish(); else if (acq) C.stage_acquire();
  shadow();
  wg_wait<0>();
  reg_fence(acc);
  C.release(c1);
  if (reload) {
    const Cur a0 = cur; cur.adv();
    const Cur a1 = cur; cur.adv();
    proj_load_a<2 - I>(C, a0, a);
    proj_load_a<3 - I>(C, a1, a);
    bar_sync(4 + C.w + loaded<16>(a + 64 - 32 * I, C.zero), 128);
    C.release(a0); C.release(a1);
  }
}

__global__ void __cluster_dims__(2, 1, 1) __launch_bounds__(384, 1) fused_kernel(const __grid_constant__ Params P) {
  extern __shared__ uint8_t smem_raw[];
  uint8_t* smem = smem_raw + ((1024 - (smem_u32(smem_raw) & 1023)) & 1023);
  const int tid = threadIdx.x;
  const uint32_t sb = smem_u32(smem);
  const uint32_t full0 = sb + SMEM_BAR, empty0 = full0 + 8 * NSLOT, stgf0 = empty0 + 8 * NSLOT, stge0 = stgf0 + 16, gate0 = stge0 + 16, evt0 = gate0 + 64;
  const int warp = __shfl_sync(~0u, tid >> 5, 0);
  if (warp < 5 && elect_one()) {
#pragma unroll
    for (int i = 0; i < 6; i++) mbar_init(full0 + 48 * warp + 8 * i, warp == 1 ? 4 : warp == 2 && i < 2 ? 128 : 1);
    asm volatile("fence.mbarrier_init.release.cluster;" ::: "memory");
  }
  __syncwarp();
  asm volatile("barrier.cluster.arrive.relaxed.aligned;" ::: "memory");
  const int c = P.role[blockIdx.x >> 1], r = blockIdx.x & 1;
  const bool spare = blockIdx.x >= 128;
  const int vb = 2 * c + r;
  const int rp = c & 7, g = c >> 3;
  const int rb = 2 * rp + r;
  const int j3 = (c >> 1) & 15, ks = (rp ^ (rp >> 1)) & 1, ncol = 2 * (c >> 5) + r;
  const int wg = warp >> 2;
  volatile unsigned* const ep_smem = (volatile unsigned*)(smem + SMEM_BAR + 240);

  if (wg == 0) {
    const CUtensorMap* const w0 = spare ? &P.wuv : &P.wuk;
    if (warp == 0 && elect_one()) {
      mbar_expect(full0, TILE);
      tma_load(sb, &P.ckv, 0, rb * 128, full0);
      tma_load(sb + HALF, &P.ckv, 64, rb * 128, full0);
      tma_load(sb + TILE, w0, (4 * g + 3) * 128, 0, full0 + 8);
      tma_load(sb + TILE + HALF, w0, (4 * g + 3) * 128 + 64, 0, full0 + 8);
#pragma unroll
      for (int i = 1; i < NSLOT; i++) mbar_expect(full0 + 8 * i, TILE);
    }
    __syncwarp();
    asm volatile("setmaxnreg.dec.sync.aligned.u32 24;");
    asm volatile("barrier.cluster.wait.aligned;" ::: "memory");
    if (warp == 0 && elect_one()) {
#pragma unroll
      for (int i = 1; i < 3; i++) {
        tma_load(sb + 2 * i * TILE, &P.ckv, 128 * i, rb * 128, full0 + 16 * i);
        tma_load(sb + 2 * i * TILE + HALF, &P.ckv, 128 * i + 64, rb * 128, full0 + 16 * i);
        tma_load_mc(sb + (2 * i + 1) * TILE + r * HALF, w0, (4 * g + 3) * 128 + 64 * r, 128 * i, full0 + 16 * i + 8);
      }
    }
    __syncwarp();
    if (warp == 0) {
      if (elect_one()) {
        Cur cur{0, 1};
        uint32_t dst, bar;
        auto acquire = [&](int bytes = TILE) {
          mbar_wait(empty0 + cur.o, cur.phase ^ 1);
          dst = sb + cur.o * (TILE / 8); bar = full0 + cur.o;
          mbar_expect(bar, bytes);
          cur.adv();
        };
        auto load_a = [&](const CUtensorMap* am, int rows, int i, int extra = 0) {
          acquire(TILE + extra);
          tma_load(dst, am, 128 * i, rows * 128, bar);
          tma_load(dst + HALF, am, 128 * i + 64, rows * 128, bar);
        };
        for (int u = 0; u < (spare ? 16 : 12); u++) {
          if (u == 1 && !ks && !spare) continue;
          const CUtensorMap* wm = spare ? &P.wuv : u >= 8 ? &P.wq : ((u & 1) ? &P.wuv : &P.wuk);
          const int head = spare ? 4 * (u & 7) + 3 : 4 * g + (u >= 8 ? (0x0231 >> (4 * (u - 8))) & 3 : 3 - (u >> 1));
          if (u == 6 && !spare) {
            l2_prefetch(g_xn + (size_t)(rb * 128 + 16 * g) * DM, HALF);
            tma_prefetch(&P.wq, (4 * g + 1 + 2 * (rp >> 2)) * 128 + 64 * r, 128 * (rp & 3));
          }
          if (u == 8 && !spare) mbar_wait(gate0, 0);
#pragma unroll 1
          for (int i = u == 0 ? 3 : 0; i < 4; i++) {
#pragma unroll 1
            for (int k = i; k <= (u == 0 ? i : u == 8 && !(i & 1) ? i + 1 : -1); k++) {
              const int extra = u == 0 ? 1024 : 0;
              load_a(u == 0 || spare ? &P.ckv : &P.xn, spare ? rb + u : rb, k, extra);
              if (extra) bulk_load(sb + SMEM_WR, P.w_r, 1024, bar);
            }
            acquire();
            tma_load_mc(dst + r * HALF, wm, head * 128 + 64 * r, 128 * i, bar);
          }
        }
        if (!spare) {
          const uint8_t* pv = nullptr;
          int pmode = 0;
          auto load_kv = [&](const uint8_t* tile, int mode) {
            acquire(mode == 2 ? 0 : TILE);
            if (mode == 0) bulk_load_mc(dst + r * HALF, tile + r * HALF, HALF, bar);
            else if (mode == 1) bulk_load(dst, tile, TILE, bar);
          };
          mbar_wait(gate0 + 8, 0);
          for (int it = 0; it < 4; it++) {
            const int j = item_rows(rb, it);
            if (it == 3) mbar_wait(gate0 + 56, 0);
            for (int b = 0; b <= (j | 1); b++) {
              const int mode = b < (j | 1) ? 0 : b == j ? 1 : 2;
              if (mode == 2 && it < 3) {
                mbar_wait(gate0 + (it ? 24 : 16), 0);
                load_kv(P.tile(0, 4 * g + it + 1, item_rows(rb, it + 1)), 1);
              } else {
                load_kv(P.tile(1, 4 * g + it, b), mode);
              }
              if (pv) load_kv(pv, pmode);
              pv = P.tile(2, 4 * g + it, b);
              pmode = mode;
              if (rp == 4 && it == 1 && b >= 4 && b < 7) l2_prefetch(P.tile(1, 4 * g + 3, b - 4) + r * HALF, HALF);
            }
          }
          load_kv(pv, pmode);
          mbar_wait(gate0 + 32, 0);
#pragma unroll 1
          for (int tt = ks ? KSH : -KSH; tt < 32; tt++) {
            const int t = tt < 0 ? tt + KSH : tt;
            const int head = (tt < 0 ? 16 : 16 * ks) + 4 * ((t >> 1) & 3) + (t >> 3);
            if (t == 16 || t == 24) mbar_wait(gate0 + 24 + t, 0);
            acquire();
            bulk_load_mc(dst + r * 8192, P.tile(0, head, j3) + (t & 1) * HALF + r * 8192, 8192, bar);
            tma_load(dst + HALF, &P.wo, ncol * 128, head * 128 + (t & 1) * 64, bar);
            tma_load(dst + HALF + 8192, &P.wo, ncol * 128 + 64, head * 128 + (t & 1) * 64, bar);
          }
          mbar_wait(gate0, 1);
          acquire();
#pragma unroll 1
          for (int i = 0; i < 4; i++) tma_load(dst + i * 8192, i < 2 ? &P.x64 : &P.xn64, ncol * 128 + 64 * (i & 1), j3 * 128 + 64 * (ks ^ 1), bar);
        }
#pragma unroll 1
        for (int i = 0; i < NSLOT; i++) { mbar_wait(empty0 + cur.o, cur.phase ^ 1); cur.adv(); }
      }
    } else if (warp == 3) {
      if (!spare) bar_sync(3, 288);
      if (!spare && elect_one()) {
        flag_add(F_LN + rb);
        const unsigned ep = g_epoch[blockIdx.x] + 1;
        *ep_smem = ep;
        g_epoch[blockIdx.x] = ep;
        for (int i = 0; i < 7; i++) {
          if (i) mbar_wait(evt0 + 8 * (i - 1), 0);
          if (i == 4) flag_wait(F_CTX + j3 * 6 + 3, ep * 16);
          flag_wait(i == 0 ? F_LN + rb : i < 4 ? F_GRP + 3 * g + i - 1 : F_CTX + j3 * 6 + ks * 3 + i - 4, ep * (i == 0 || i > 4 ? 8 : i < 4 ? 32 : 16));
          fence_async_global();
          mbar_arrive(gate0 + 8 * i);
          if (i == 3) { flag_wait<500>(F_VD, ep * 8); fence_async_global(); mbar_arrive(gate0 + 56); }
        }
        flag_wait(F_MOE, ep);
        fence_async_global();
        mbar_arrive(gate0);
      }
    } else {
      if (elect_one()) {
        const int w = warp - 1;
        const uint32_t stg = sb + SMEM_STG + w * HALF;
        uint32_t phase = 0;
        for (int job = 0; job < (spare ? 16 : 15); job++) {
          if (job == 1 && !ks && !spare) continue;
          int tile, flag = -1;
          if (spare) {
            tile = (2 * NH + 4 * (job & 7) + 3) * 16 + rb + (job & 8);
            if (job == 15) flag = F_VD;
          } else if (job < 8) {
            tile = ((1 + (job & 1)) * NH + 4 * g + 3 - (job >> 1)) * 16 + rb;
            if (job == 7) flag = F_GRP + 3 * g;
          } else if (job < 11) {
            tile = (4 * g + ((0x231 >> (4 * (job - 8))) & 3)) * 16 + rb;
            if (job != 9) flag = F_GRP + 3 * g + (job >> 1) - 3;
          } else {
            const int it = job - 11;
            const int j = item_rows(rb, it);
            tile = (4 * g + it) * 16 + j;
            flag = F_CTX + j * 6 + (g >> 2) * 3 + max(it - 1, 0);
          }
          uint8_t* d = P.tile(0, 0, tile) + w * 8192;
          mbar_wait(stgf0 + 8 * w, phase);
          phase ^= 1;
          bulk_store(d, stg, 8192);
          bulk_store(d + HALF, stg + 8192, 8192);
          asm volatile("cp.async.bulk.commit_group;" ::: "memory");
          asm volatile("cp.async.bulk.wait_group.read 0;" ::: "memory");
          if (!spare && job >= 10 && job < 13 && (item_rows(rb, job - 10) & 1)) {
            const int it = job - 9;
            mbar_wait(gate0 + (it > 1 ? 24 : 16), 0);
            const uint8_t* q = P.tile(0, 4 * g + it, item_rows(rb, it)) + w * 8192;
            mbar_expect(stge0 + 8 * w, HALF);
            bulk_load(stg, q, 8192, stge0 + 8 * w);
            bulk_load(stg + 8192, q + HALF, 8192, stge0 + 8 * w);
          } else {
            mbar_arrive(stge0 + 8 * w);
          }
          if (flag >= 0) {
            asm volatile("cp.async.bulk.wait_group 0;" ::: "memory");
            fence_async_global();
            flag_add(flag);
            if (w == 1 && job != 11 && !spare) mbar_arrive(evt0 + 8 * (job < 12 ? (job >> 1) - 3 : job - 9));
          }
        }
      }
    }
  } else {
    asm volatile("setmaxnreg.inc.sync.aligned.u32 240;");
    const int t = tid & 127, lane = tid & 31, wi = t >> 5;
    Ctx C;
    C.neg = P.neg; C.zero = P.zero; C.sb = sb; C.dlo = desc_lo(sb); C.full0 = full0; C.w = wg - 1;
    asm("mapa.shared::cluster.u32 %0, %1, %2;" : "=r"(C.rel) : "r"(empty0), "r"(lane & 1));
    C.rel_pred = t < 2;
    C.warp0 = (warp & 3) == 0;
    C.stg = sb + SMEM_STG + C.w * HALF;
    C.stg_full = stgf0 + 8 * C.w; C.stg_empty = stge0 + 8 * C.w; C.stg_phase = 0;
    C.frag_off = (16 * wi + (lane & 15)) * 128;
    C.frag_x = ((lane >> 4) ^ (lane & 7)) * 16;
    asm volatile("barrier.cluster.wait.aligned;" ::: "memory");
    asm volatile("st.shared.u32 [%0], %1;" :: "r"(full0 + 244 + 4 * C.w), "r"(0) : "memory");
    if (C.w == 1) bar_arrive(1, 256);
    Cur cur{C.zero, 0};
    Attn A;
    {
      uint32_t a[128];
      float acc[64];
      LayerNorm ln;
      const int ln_off = (rb * 128 + 16 * g + ((tid >> 4) & 15)) * DM + 8 * (tid & 15);
      proj_step_first<0>(C, cur, a, acc, ln, P.px, ln_off);
      proj_step_first<1>(C, cur, a, acc, ln, P.px, ln_off);
      proj_step_first<2>(C, cur, a, acc, ln, P.px, ln_off);
      proj_step_first<3>(C, cur, a, acc, ln, P.px, ln_off);
      C.stage_out<false>(acc, 1.f, 1.f);
      auto route = [&]() { ln.route(sb + SMEM_WR + 16 * (tid & 15), g_r + (ln_off >> 9)); bar_arrive(3, 288); };
      proj_step2<0>(C, cur, a, acc, false, false, [&]() { if (!spare) { ln.stats(); pin(ln.rs, C.neg, C.stg_full); } });
      proj_step2<2>(C, cur, a, acc, true, false, [&]() { if (!spare) ln.store(g_xn + ln_off); });
#pragma unroll 1
      for (int u = ks || spare ? 2 : 3; u < (spare ? 16 : 12); u++) {
        if (u > 8 && !spare) C.stage_out<true>(acc, SM_SCALE, SM_SCALE);
        else C.stage_out<false>(acc, 1.f, 1.f);
        proj_step2<0>(C, cur, a, acc, false, u == 8, [&]() { if (u == 3 && !spare) route(); });
        proj_step2<2>(C, cur, a, acc, u < 11 || spare, u == 7, []() {});
      }
      if (spare) {
        C.stage_out<false>(acc, 1.f, 1.f);
        C.publish();
        if (C.w == 0) C.turn_begin();
        const unsigned ep = g_epoch[blockIdx.x] + 1;
        C.stage_acquire();
        bar_sync(6, 256);
        moe_cta(P, blockIdx.x - 128, ep, smem);
        if (tid == 128) { g_epoch[blockIdx.x] = ep; }
        return;
      }
#pragma unroll
      for (int i = 0; i < 32; i++) A.q[i] = pack_bf16(acc[2 * i] * SM_SCALE, acc[2 * i + 1] * SM_SCALE);
    }
    {
      const int rel = 64 * C.w + 16 * wi + (lane >> 2) - 2 * (lane & 3);
      int it = 0, j = rb, b = 0;
      float a[4];
      A.tracked = false;
      round_first(C, A, cur, j == 0, rel, a);
      auto accept = [&](bool reject) {
        const float b0 = a[0] + a[1], b1 = a[2] + a[3];
        const bool ok = __all_sync(~0u, b0 + b1 <= (reject ? -1.f : SUM_MAX));
        if (ok) { A.l0 += b0; A.l1 += b1; }
        return ok;
      };
      if (!accept(false)) goto fallback;
#pragma unroll 1
      for (;;) {
        if (++b < (A.tracked ? 0 : j)) {
          round_step<0>(C, A, cur, b > 1, b == 1 && it > 0, b == 2 && it > 0, rel, a);
          if (accept(A.tracked)) continue;
        } else if (b > j) {
          if (it == 3) break;
          const int pj = j;
          it++; j = item_rows(rb, it); b = 0;
          round_begin(C, A, cur, !(pj & 1), pj > 0, j == 0, j <= 1, rel, a);
          if (accept(false)) continue;
        } else if (A.tracked) {
          goto tracked_round;
        } else if (C.w) {
          round_step<1>(C, A, cur, b > 1, false, b == 2 && it > 0, rel, a);
          if (accept(A.tracked)) continue;
        } else {
          round_step<2>(C, A, cur, b > 1, false, b == 2 && it > 0, rel, a);
          if (accept(A.tracked)) continue;
        }
      fallback:
        redo_block(A, P.tile(1, 4 * g + it, b), b == 0, b == j, rel);
        C.set_tracked();
        if (!C.zero) continue;
      tracked_round:
        round_step<3>(C, A, cur, b > 1, b == 1 && it > 0 && j > 1, b == 2 && it > 0, b < j ? 128 : rel, a);
        A.l0 += a[0] + a[1]; A.l1 += a[2] + a[3];
      }
      const bool skip = !(j & 1);
      if (skip) { C.release(cur); cur.adv(); C.wait(cur); }
      const Cur cv = cur; cur.adv();
      C.turn_begin();
      issue_pv(A, C.dsc(cv), j > 0, C.w);
      if (C.w == 0) bar_arrive(2, 256);
      if (skip) { C.skip(cur); cur.adv(); }
      float r0, r1;
      inv_sums(A, r0, r1);
      float acc[64];
      auto issue_out = [&](const Cur& cs, int accumulate) {
        C.wait(cs);
        wg_fence();
        const uint32_t da = C.dsc(cs) + (C.w ^ ks) * 512, db = C.dsc(cs) + (HALF >> 4) - ((8192 >> 4) << 16);
#pragma unroll
        for (int kk = 0; kk < 4; kk++)
          wgmma_ss_n128<1>(acc, desc(da + ((kk * 32) >> 4)), desc(db + ((kk * 2048) >> 4)), kk > 0 ? 1 : accumulate);
        wg_commit();
      };
      const Cur c0 = cur; cur.adv();
      Cur prev = cur; cur.adv();
      C.stage_acquire();
      wg_wait<0>();
      reg_fence(A.o);
      C.release(cv);
      C.stage_out<true>(A.o, r0, r1);
      C.publish();
      issue_out(c0, 0);
      issue_out(prev, 1);
      wg_wait<1>();
      C.release(c0);
      uint4* const mine = g_part + (size_t)vb * 1024 + t;
      const uint32_t tag = *ep_smem & 1;
      if (C.w == 0) { st_msg(mine + 3 * 128, tag ^ 1, 0, 0, 0); st_msg(mine + 7 * 128, tag ^ 1, 0, 0, 0); }
#pragma unroll 1
      for (int h = ks ? 2 + KSH : 2 - KSH; h < 32; h++) {
        const Cur cs = cur; cur.adv();
        const bool hold = C.w && h == 32 - LEAD;
        if (hold) { wg_wait<0>(); C.release(prev); bar_sync(7, 256); }
        issue_out(cs, 1);
        if (h == 31) break;
        wg_wait<1>();
        if (!hold) C.release(prev);
        prev = cs;
      }
      const Cur last{cur.o ? cur.o - 8 : 40, 0}, cr = cur;
      uint32_t xr[16], nr[16];
      uint4 v[4];
      const uint32_t xa = C.addr(cr) + (C.w ^ 1) * 8192;
      auto receive = [&]() {
        const uint4* theirs = g_part + (size_t)(vb ^ 2) * 1024 + (C.w ^ 1) * 512 + t;
        C.wait(cr);
#pragma unroll
        for (int jj = 0; jj < 4; jj++) {
          ldsm4(xa + C.frag(jj, 0), xr[4 * jj], xr[4 * jj + 1], xr[4 * jj + 2], xr[4 * jj + 3]);
          ldsm4(xa + HALF + C.frag(jj, 0), nr[4 * jj], nr[4 * jj + 1], nr[4 * jj + 2], nr[4 * jj + 3]);
        }
#pragma unroll 1
        for (int n = 0; n < SPIN_LIMIT; n++) {
          v[3] = ld_msg(theirs + 3 * 128);
          if (!__all_sync(~0u, ((v[3].x ^ tag) & 1) == 0)) continue;
#pragma unroll
          for (int i = 0; i < 3; i++) v[i] = ld_msg(theirs + i * 128);
          if (__all_sync(~0u, (((v[0].x ^ tag) | (v[1].x ^ tag) | (v[2].x ^ tag)) & 1) == 0)) break;
        }
      };
      const uint32_t pass = sb + SMEM_STG + HALF + t * 16;
      float y[32];
      if (C.w == 0) {
        bar_arrive(7, 256);
        wg_wait<0>();
        reg_fence(acc);
#pragma unroll
        for (int i = 0; i < 8; i++)
          st_msg(mine + i * 128, (pack_bf16(__uint_as_float((__float_as_uint(acc[8 * i]) + 0x10000u) & 0xfffe0000u), acc[8 * i + 1]) & ~1u) | tag,
                 pack_bf16(acc[8 * i + 2], acc[8 * i + 3]), pack_bf16(acc[8 * i + 4], acc[8 * i + 5]), pack_bf16(acc[8 * i + 6], acc[8 * i + 7]));
        receive();
        bar_sync(6, 256);
#pragma unroll
        for (int i = 0; i < 8; i++)
          asm volatile("ld.shared.v4.f32 {%0, %1, %2, %3}, [%4];" : "=f"(y[4 * i]), "=f"(y[4 * i + 1]), "=f"(y[4 * i + 2]), "=f"(y[4 * i + 3]) : "r"(pass + i * 2048) : "memory");
      } else {
        C.stage_acquire();
        receive();
        wg_wait<0>();
        reg_fence(acc);
#pragma unroll
        for (int i = 0; i < 8; i++)
          asm volatile("st.shared.v4.f32 [%0], {%1, %2, %3, %4};" :: "r"(pass + i * 2048), "f"(acc[32 + 4 * i]), "f"(acc[33 + 4 * i]), "f"(acc[34 + 4 * i]), "f"(acc[35 + 4 * i]) : "memory");
        bar_arrive(6, 256);
#pragma unroll
        for (int i = 0; i < 32; i++) y[i] = acc[i];
      }
      C.release(prev); C.release(last); C.release(cr);
#pragma unroll
      for (int i = 0; i < 4; i++) {
        const uint32_t u[4] = {v[i].x & ~1u, v[i].y, v[i].z, v[i].w};
#pragma unroll
        for (int k = 0; k < 4; k++)
          xr[4 * i + k] = add_bf16x2(add_bf16x2(xr[4 * i + k], pack_bf16(y[8 * i + 2 * k] + bf_lo(u[k]), y[8 * i + 2 * k + 1] + bf_hi(u[k]))), nr[4 * i + k]);
        stsm4(xa + C.frag(i, 0), xr[4 * i], xr[4 * i + 1], xr[4 * i + 2], xr[4 * i + 3]);
      }
      __syncwarp();
      __nv_bfloat16* po = P.out + (size_t)(j3 * 128 + 64 * (ks ^ 1) + 16 * wi + (lane >> 3)) * DM + ncol * 128 + 64 * (C.w ^ 1) + (lane & 7) * 8;
#pragma unroll
      for (int i = 0; i < 4; i++) {
        const int row = 16 * wi + 4 * i + (lane >> 3);
        uint4 z;
        asm volatile("ld.shared.v4.u32 {%0, %1, %2, %3}, [%4];" : "=r"(z.x), "=r"(z.y), "=r"(z.z), "=r"(z.w) : "r"(xa + row * 128 + (((lane ^ row) & 7) << 4)) : "memory");
        *(uint4*)(po + 4 * i * DM) = z;
      }
    }
  }
}

typedef CUresult (*EncodeFn)(CUtensorMap*, CUtensorMapDataType, cuuint32_t, void*, const cuuint64_t*, const cuuint64_t*,
                             const cuuint32_t*, const cuuint32_t*, CUtensorMapInterleave, CUtensorMapSwizzle,
                             CUtensorMapL2promotion, CUtensorMapFloatOOBfill);

void make_map(EncodeFn fn, CUtensorMap* m, const void* ptr, uint64_t cols, uint64_t rows, uint32_t box_rows) {
  cuuint64_t dims[2] = {cols, rows};
  cuuint64_t strides[1] = {cols * 2};
  cuuint32_t box[2] = {64, box_rows};
  cuuint32_t es[2] = {1, 1};
  fn(m, CU_TENSOR_MAP_DATA_TYPE_BFLOAT16, 2, const_cast<void*>(ptr), dims, strides, box, es, CU_TENSOR_MAP_INTERLEAVE_NONE,
     CU_TENSOR_MAP_SWIZZLE_128B, CU_TENSOR_MAP_L2_PROMOTION_L2_256B, CU_TENSOR_MAP_FLOAT_OOB_FILL_NONE);
}

}

extern "C" void kernel_launch(void* const* d_in, const int* in_sizes, int n_in, void* d_out, int out_size) {
  static EncodeFn fn = nullptr;
  static void *xn_ptr = nullptr, *qkv_ptr = nullptr;
  if (!fn) {
    void* f = nullptr;
    cudaDriverEntryPointQueryResult qr;
    cudaGetDriverEntryPoint("cuTensorMapEncodeTiled", &f, cudaEnableDefault, &qr);
    fn = (EncodeFn)f;
    cudaGetSymbolAddress(&xn_ptr, g_xn);
    cudaGetSymbolAddress(&qkv_ptr, g_qkv);
    cudaFuncSetAttribute(fused_kernel, cudaFuncAttributeMaxDynamicSharedMemorySize, SMEM_TOTAL);
  }
  Params P;
  make_map(fn, &P.x64, d_in[0], DM, SEQ, 64);
  make_map(fn, &P.xn64, xn_ptr, DM, SEQ, 64);
  make_map(fn, &P.ckv, d_in[1], DM, SEQ, 128);
  make_map(fn, &P.xn, xn_ptr, DM, SEQ, 128);
  make_map(fn, &P.wq, d_in[2], NH * 128, DM, 128);
  make_map(fn, &P.wuk, d_in[3], NH * 128, DM, 128);
  make_map(fn, &P.wuv, d_in[4], NH * 128, DM, 128);
  make_map(fn, &P.wo, d_in[5], DM, NH * 128, 64);
  P.out = (__nv_bfloat16*)d_out;
  P.qkv = (uint8_t*)(((uintptr_t)qkv_ptr + (2 << 20) - 1) & ~(uintptr_t)((2 << 20) - 1));
  for (int i = 0; i < 64; i++) {
    const int c = i < 4 ? 4 + i : i < 36 ? ((i - 4) & 7) * 8 + ((i - 4) >> 3) : (1 + (i - 36) % 7) * 8 + 4 + (i - 36) / 7;
    P.role[i] = (c & 32) | ((c & 3) << 3) | ((c >> 2) & 7);
  }
  P.role[64] = 0; P.role[65] = 3;
  P.neg = -1.f;
  P.zero = 0;
  P.px = (const __nv_bfloat16*)d_in[0];
  P.w_r = (const __nv_bfloat16*)d_in[7];
  P.w_gate = (const __nv_bfloat16*)d_in[8];
  P.w_up = (const __nv_bfloat16*)d_in[9];
  P.w_down = (const __nv_bfloat16*)d_in[10];
  fused_kernel<<<NCTA, 384, SMEM_TOTAL>>>(P);
}
```
